```python
import torch

def _softmax(x, axis=-1):
    return torch.softmax(x, dim=axis)
def _gelu(x):
    return torch.nn.functional.gelu(x, approximate="tanh")
def _silu(x):
    return torch.nn.functional.silu(x)
def _sigmoid(x):
    return torch.sigmoid(x)
def _layernorm(x, axis=-1, eps=1e-5):
    m = x.mean(dim=axis, keepdim=True)
    v = x.var(dim=axis, keepdim=True, unbiased=False)
    return (x - m) / torch.sqrt(v + eps)
def _scatter_add(tgt, idx, src, axis=0):
    return tgt.clone().index_add_(axis, idx, src)
def _segment_sum(src, seg, n):
    out = torch.zeros((n,) + src.shape[1:], dtype=src.dtype)
    return out.index_add_(0, seg, src)
def _pad(x, pw):
    flat = tuple(v for pair in reversed(pw) for v in pair)
    return torch.nn.functional.pad(x, flat)

kernel_name = 'interleave_layers__gqa_block_cached__sliding_block_cached__decode'

def setup_inputs():

    _w = (lambda a: (lambda t: t.to(torch.bfloat16) if t.is_floating_point() else t)(torch.as_tensor(a)))
    def _A_setup():
        B, Sq, D = 1, 1, 512
        Hq, Hkv, Sk, Dh = 32, 8, 32768, 128
        assert Hq % Hkv == 0, (Hq, Hkv)
        return {
            "x": _w((lambda *s: torch.randn(*s, dtype=torch.bfloat16) * 0.1)(B, Sq, D)),
            "k_cache": _w((lambda *s: torch.randn(*s, dtype=torch.bfloat16) * 0.8)(B, Hkv, Sk, Dh)),
            "v_cache": _w((lambda *s: torch.randn(*s, dtype=torch.bfloat16) * 3.2)(B, Hkv, Sk, Dh)),
            "wq": _w((lambda *s: torch.randn(*s, dtype=torch.bfloat16) * 0.8)(D, Hq * Dh) * (D ** -0.5)),
            "wo": _w((lambda *s: torch.randn(*s, dtype=torch.bfloat16) * 3.2)(Hq * Dh, D) * ((Hq * Dh) ** -0.5)),
        }
    _A_in = _A_setup()

    def _B_setup():
        B, Sq, D = 1, 1, 512
        Hq, Hkv, Sk, Dh = 32, 8, 32768, 128
        assert Hq % Hkv == 0, (Hq, Hkv)
        return {
            "x": _w((lambda *s: torch.randn(*s, dtype=torch.bfloat16) * 0.1)(B, Sq, D)),
            "k_cache": _w((lambda *s: torch.randn(*s, dtype=torch.bfloat16) * 0.8)(B, Hkv, Sk, Dh)),
            "v_cache": _w((lambda *s: torch.randn(*s, dtype=torch.bfloat16) * 1.6)(B, Hkv, Sk, Dh)),
            "wq": _w((lambda *s: torch.randn(*s, dtype=torch.bfloat16) * 0.8)(D, Hq * Dh) * (D ** -0.5)),
            "wo": _w((lambda *s: torch.randn(*s, dtype=torch.bfloat16) * 1.6)(Hq * Dh, D) * ((Hq * Dh) ** -0.5)),
        }
    _B_in = _B_setup()

    return {
        "A_x": _A_in["x"],
        "A_k_cache": _A_in["k_cache"],
        "A_v_cache": _A_in["v_cache"],
        "A_wq": _A_in["wq"],
        "A_wo": _A_in["wo"],
        "B_x": _B_in["x"],
        "B_k_cache": _B_in["k_cache"],
        "B_v_cache": _B_in["v_cache"],
        "B_wq": _B_in["wq"],
        "B_wo": _B_in["wo"],
    }

def reference(A_x, A_k_cache, A_v_cache, A_wq, A_wo, B_x, B_k_cache, B_v_cache, B_wq, B_wo):
    def _A_ref(x, k_cache, v_cache, wq, wo):
        B, Sq, D = x.shape
        Hq, Dh = 32, 128
        Hkv = k_cache.shape[1]
        rep = Hq // Hkv
        q = (lambda x, *d: x.permute(*d))((x @ wq).reshape(B, Sq, Hq, Dh), 0, 2, 1, 3)
        k = (lambda x, n, axis: torch.repeat_interleave(x, n, dim=axis))(k_cache, rep, axis=1)
        v = (lambda x, n, axis: torch.repeat_interleave(x, n, dim=axis))(v_cache, rep, axis=1)
        scores = torch.einsum("bhqd,bhkd->bhqk", q, k) * (Dh ** -0.5)
        p = _softmax(scores, axis=-1)
        o = torch.einsum("bhqk,bhkd->bhqd", p, v)
        return (lambda x, *d: x.permute(*d))(o, 0, 2, 1, 3).reshape(B, Sq, Hq * Dh) @ wo

    def _B_ref(x, k_cache, v_cache, wq, wo):
        B, Sq, D = x.shape
        Hq, Dh = 32, 128
        Hkv, Sk = k_cache.shape[1], k_cache.shape[2]
        W = min(4096, max(256, Sk // 4))
        rep = Hq // Hkv
        q = (lambda x, *d: x.permute(*d))((x @ wq).reshape(B, Sq, Hq, Dh), 0, 2, 1, 3)
        k = (lambda x, n, axis: torch.repeat_interleave(x, n, dim=axis))(k_cache[:, :, Sk - W:, :], rep, axis=1)
        v = (lambda x, n, axis: torch.repeat_interleave(x, n, dim=axis))(v_cache[:, :, Sk - W:, :], rep, axis=1)
        scores = torch.einsum("bhqd,bhkd->bhqk", q, k) * (Dh ** -0.5)
        p = _softmax(scores, axis=-1)
        o = torch.einsum("bhqk,bhkd->bhqd", p, v)
        return (lambda x, *d: x.permute(*d))(o, 0, 2, 1, 3).reshape(B, Sq, Hq * Dh) @ wo

    x = A_x
    x = x + _A_ref(_layernorm(x, axis=-1), A_k_cache, A_v_cache, A_wq, A_wo)
    x = x + _B_ref(_layernorm(x, axis=-1), B_k_cache, B_v_cache, B_wq, B_wo)
    x = x + _A_ref(_layernorm(x, axis=-1), A_k_cache, A_v_cache, A_wq, A_wo)
    x = x + _B_ref(_layernorm(x, axis=-1), B_k_cache, B_v_cache, B_wq, B_wo)
    return x
```

```cpp
#include <cuda_runtime.h>
#include <cuda_bf16.h>
#include <cuda.h>
#include <stdint.h>

namespace {

constexpr int NCTA  = 128;
constexpr int NW    = 8;
constexpr int NSLOT = 7;
constexpr int TILE  = 4096;
constexpr int NFIRST = 3;
#define NRF 3

constexpr int OFF_BAR = NW * NSLOT * TILE;
constexpr int OFF_RED = OFF_BAR + 512;
constexpr int OFF_ST  = OFF_RED + 2048;
constexpr int OFF_ML  = OFF_ST + 64;
constexpr int SMEM_BYTES = OFF_ML + 256;

constexpr uint64_t POL_EVICT_FIRST = 0x12F0000000000000ull;
constexpr int SPIN_LIMIT = 1 << 20;
constexpr unsigned FULL = 0xffffffffu;

enum { M_KA = 0, M_VA = 1, M_KB = 2, M_VB = 3, M_WQA = 4, M_WQB = 5, M_WOA = 6, M_WOB = 7 };

constexpr uint32_t STEP_RF = 1u << 13, STEP_LAST = 1u << 14;
struct Xchg {
    float q[NCTA][32];
    float part[NCTA][NW][96];
    float x[2][NCTA][32];
};
struct __align__(64) Params {
    CUtensorMap maps[8];
    const __nv_bfloat16* x;
    __nv_bfloat16* out;
    Xchg* xc;
    int nsecond;
    uint32_t steps[80];
};
__device__ __align__(128) Xchg g_xchg;
#define TSTAMP(i)

__device__ __forceinline__ int lane_id() { int l; asm volatile("mov.u32 %0, %%laneid;" : "=r"(l)); return l; }
__device__ __forceinline__ bool mbar_try(uint32_t bar, uint32_t parity) {
    uint32_t ok;
    asm volatile("{\n.reg .pred p;\nmbarrier.try_wait.parity.shared::cta.b64 p, [%1], %2;\nselp.u32 %0, 1, 0, p;\n}"
                 : "=r"(ok) : "r"(bar), "r"(parity) : "memory");
    return __all_sync(0xffffffffu, ok);
}
__device__ __forceinline__ void mbar_wait(uint32_t bar, uint32_t parity) {
    if (!mbar_try(bar, parity)) {
        int n = 0;
        while (!mbar_try(bar, parity) && ++n < (1 << 17)) {}
    }
}
__device__ __forceinline__ void ldsm4(uint32_t* r, uint32_t a) {
    asm volatile("ldmatrix.sync.aligned.m8n8.x4.shared.b16 {%0,%1,%2,%3}, [%4];"
                 : "=r"(r[0]), "=r"(r[1]), "=r"(r[2]), "=r"(r[3]) : "r"(a) : "memory");
}
__device__ __forceinline__ void ldsm4t(uint32_t* r, uint32_t a) {
    asm volatile("ldmatrix.sync.aligned.m8n8.x4.trans.shared.b16 {%0,%1,%2,%3}, [%4];"
                 : "=r"(r[0]), "=r"(r[1]), "=r"(r[2]), "=r"(r[3]) : "r"(a) : "memory");
}
__device__ __forceinline__ void mma16816(float* c, uint32_t a0, uint32_t a1, uint32_t a2, uint32_t a3, uint32_t b0, uint32_t b1) {
    asm volatile("mma.sync.aligned.m16n8k16.row.col.f32.bf16.bf16.f32 {%0,%1,%2,%3}, {%4,%5,%6,%7}, {%8,%9}, {%0,%1,%2,%3};"
                 : "+f"(c[0]), "+f"(c[1]), "+f"(c[2]), "+f"(c[3])
                 : "r"(a0), "r"(a1), "r"(a2), "r"(a3), "r"(b0), "r"(b1));
}
__device__ __forceinline__ void mma16816(float* c, const uint32_t* a, uint32_t b0, uint32_t b1) { mma16816(c, a[0], a[1], a[2], a[3], b0, b1); }
__device__ __forceinline__ uint32_t movm(uint32_t a) {
    uint32_t d;
    asm volatile("movmatrix.sync.aligned.m8n8.trans.b16 %0, %1;" : "=r"(d) : "r"(a));
    return d;
}
__device__ __forceinline__ uint32_t pack_bf16(float lo, float hi) {
    uint32_t d;
    asm("cvt.rn.bf16x2.f32 %0, %1, %2;" : "=r"(d) : "f"(hi), "f"(lo));
    return d;
}
__device__ __forceinline__ float bf_lo(uint32_t v) { return __uint_as_float(v << 16); }
__device__ __forceinline__ float bf_hi(uint32_t v) { return __uint_as_float(v & 0xffff0000u); }
__device__ __forceinline__ float ex2(float v) { float d; asm("ex2.approx.ftz.f32 %0, %1;" : "=f"(d) : "f"(v)); return d; }
__device__ __forceinline__ float lg2(float v) { float d; asm("lg2.approx.ftz.f32 %0, %1;" : "=f"(d) : "f"(v)); return d; }
__device__ __forceinline__ float rcp(float v) { float d; asm("rcp.approx.ftz.f32 %0, %1;" : "=f"(d) : "f"(v)); return d; }
__device__ __forceinline__ float rsq(float v) { float d; asm("rsqrt.approx.ftz.f32 %0, %1;" : "=f"(d) : "f"(v)); return d; }
__device__ __forceinline__ uint32_t tagged(float v, uint32_t tag) { return (__float_as_uint(v) & ~3u) | tag; }

__device__ __forceinline__ void st_rlx(void* p, uint32_t a) { asm volatile("st.relaxed.gpu.global.b32 [%0], %1;" :: "l"(p), "r"(a) : "memory"); }
__device__ __forceinline__ uint32_t ld_rlx(const void* p) { uint32_t a; asm volatile("ld.relaxed.gpu.global.b32 %0, [%1];" : "=r"(a) : "l"(p) : "memory"); return a; }
__device__ __forceinline__ void st_rlx8(void* p, uint32_t a, uint32_t b) {
    asm volatile("{\n.reg .b64 l;\nmov.b64 l, {%1,%2};\nst.relaxed.gpu.global.b64 [%0], l;\n}" :: "l"(p), "r"(a), "r"(b) : "memory");
}
__device__ __forceinline__ void ld_rlx8(uint32_t& a, uint32_t& b, const void* p) {
    asm volatile("{\n.reg .b64 l;\nld.relaxed.gpu.global.b64 l, [%2];\nmov.b64 {%0,%1}, l;\n}" : "=r"(a), "=r"(b) : "l"(p) : "memory");
}
__device__ __forceinline__ void st_rlx16(void* p, uint32_t a, uint32_t b, uint32_t c, uint32_t d) {
    asm volatile("{\n.reg .b64 l, h;\n.reg .b128 v;\nmov.b64 l, {%1,%2};\nmov.b64 h, {%3,%4};\nmov.b128 v, {l,h};\n"
                 "st.relaxed.gpu.global.b128 [%0], v;\n}" :: "l"(p), "r"(a), "r"(b), "r"(c), "r"(d) : "memory");
}
__device__ __forceinline__ void ld_rlx16(uint32_t* r, const void* p) {
    asm volatile("{\n.reg .b64 l, h;\n.reg .b128 v;\nld.relaxed.gpu.global.b128 v, [%4];\nmov.b128 {l,h}, v;\n"
                 "mov.b64 {%0,%1}, l;\nmov.b64 {%2,%3}, h;\n}" : "=r"(r[0]), "=r"(r[1]), "=r"(r[2]), "=r"(r[3]) : "l"(p) : "memory");
}
__device__ __forceinline__ void sts(uint32_t a, float v) { asm volatile("st.shared.f32 [%0], %1;" :: "r"(a), "f"(v) : "memory"); }
__device__ __forceinline__ void sts2(uint32_t a, float x, float y) { asm volatile("st.shared.v2.f32 [%0], {%1,%2};" :: "r"(a), "f"(x), "f"(y) : "memory"); }
__device__ __forceinline__ void lds4(float* v, uint32_t a) { asm volatile("ld.shared.v4.f32 {%0,%1,%2,%3}, [%4];" : "=f"(v[0]), "=f"(v[1]), "=f"(v[2]), "=f"(v[3]) : "r"(a) : "memory"); }

constexpr float SCALE_LOG2E = 0.08838834764831845f * 1.4426950408889634f;
constexpr float MAX_SLACK = 8.f;

__device__ __forceinline__ uint32_t slot_addr(uint32_t wslots, uint32_t e) { return wslots + (e & 7u) * TILE; }
__device__ __forceinline__ uint32_t slot_bar(uint32_t wbars, uint32_t e) { return wbars + (e & 7u) * 8; }
__device__ __forceinline__ void wait_step(uint32_t wbars, uint32_t e) { mbar_wait(slot_bar(wbars, e), (e >> 3) & 1u); }
__device__ __forceinline__ void refill(const Params& p, uint32_t e, uint32_t wslots, uint32_t wbars, int w) {
    const unsigned char* m = reinterpret_cast<const unsigned char*>(&p.maps[0]) + ((e << 1) & 0x380u);
    const int c2 = w + ((e >> 6) & 0x78u), c3 = blockIdx.x & 15, c4 = blockIdx.x >> 4;
    asm volatile("{\n.reg .pred p, q;\n"
                 "elect.sync _|p, 0xffffffff;\n"
                 "setp.ne.and.u32 p, %8, 0, p;\n"
                 "setp.ne.and.u32 q, %9, 0, p;\n"
                 "@p mbarrier.arrive.expect_tx.shared::cta.b64 _, [%6], 4096;\n"
                 "@p cp.async.bulk.tensor.5d.shared::cluster.global.mbarrier::complete_tx::bytes.L2::cache_hint [%0], [%1, {%2,%2,%3,%4,%5}], [%6], %7;\n"
                 "@q cp.async.bulk.prefetch.tensor.5d.L2.global.tile [%1, {%2,%2,%3,%4,%5}];\n"
                 "}"
                 :: "r"(slot_addr(wslots, e >> 16)), "l"(m), "r"(0), "r"(c2), "r"(c3), "r"(c4), "r"(slot_bar(wbars, e >> 16)), "l"(POL_EVICT_FIRST),
                    "r"(e & 16u), "r"(e & 32u) : "memory");
}

struct Attn {
    uint32_t qf[8];
    float o[16];
    float n0, n1;
    float l0, l1;
};

__device__ __forceinline__ void softmax_step(Attn& a, float* s, uint32_t* b) {
    float y[8];
#pragma unroll
    for (int i = 0; i < 8; i++) s[i] += __shfl_xor_sync(FULL, s[i], 6);
#pragma unroll
    for (int i = 0; i < 8; i += 2) {
        y[i]     = fmaf(s[i],     SCALE_LOG2E, a.n0);
        y[i + 1] = fmaf(s[i + 1], SCALE_LOG2E, a.n1);
    }
    const float ymax = fmaxf(fmaxf(fmaxf(y[0], y[1]), fmaxf(y[2], y[3])), fmaxf(fmaxf(y[4], y[5]), fmaxf(y[6], y[7])));
    if (__any_sync(FULL, ymax > MAX_SLACK)) {
        const int lane = lane_id();
        const bool valid = ((lane >> 2) & 1) == ((lane >> 1) & 1);
        float t0 = valid ? fmaxf(fmaxf(s[0], s[2]), fmaxf(s[4], s[6])) * SCALE_LOG2E : -INFINITY;
        float t1 = valid ? fmaxf(fmaxf(s[1], s[3]), fmaxf(s[5], s[7])) * SCALE_LOG2E : -INFINITY;
        const float m0 = -fmaxf(a.n0, __shfl_xor_sync(FULL, a.n0, 4));
        const float m1 = -fmaxf(a.n1, __shfl_xor_sync(FULL, a.n1, 4));
#pragma unroll
        for (int d = 4; d <= 16; d <<= 1) {
            t0 = fmaxf(t0, __shfl_xor_sync(FULL, t0, d));
            t1 = fmaxf(t1, __shfl_xor_sync(FULL, t1, d));
        }
        t0 = fmaxf(t0, m0); t1 = fmaxf(t1, m1);
        const float r0 = ex2(m0 - t0), r1 = ex2(m1 - t1);
        a.n0 = valid ? -t0 : -INFINITY;
        a.n1 = valid ? -t1 : -INFINITY;
        a.l0 *= r0; a.l1 *= r1;
#pragma unroll
        for (int i = 0; i < 16; i += 2) { a.o[i] *= r0; a.o[i + 1] *= r1; }
#pragma unroll
        for (int i = 0; i < 8; i += 2) {
            y[i]     = fmaf(s[i],     SCALE_LOG2E, a.n0);
            y[i + 1] = fmaf(s[i + 1], SCALE_LOG2E, a.n1);
        }
    }
#pragma unroll
    for (int i = 0; i < 8; i++) y[i] = ex2(y[i]);
#pragma unroll
    for (int i = 0; i < 4; i++) b[i] = movm(pack_bf16(y[2 * i], y[2 * i + 1]));
    a.l0 += (y[0] + y[2]) + (y[4] + y[6]);
    a.l1 += (y[1] + y[3]) + (y[5] + y[7]);
}

template <bool STATS>
__device__ __forceinline__ void gemv_tile(uint32_t tile, uint32_t vpair, float (*c)[4], float* st, int lane) {
    const int mi = lane >> 3, r = lane & 7, t = lane & 3;
    const uint32_t a0 = tile + ((mi >> 1) * 8 + r) * 64 + (((mi & 1) ^ (r >> 1)) << 4);
    const int src = (t >> 1) + 16 * (t & 1);
#pragma unroll
    for (int i = 0; i < 4; i++) { c[0][i] = 0.f; c[1][i] = 0.f; if (STATS) st[i] = 0.f; }
#pragma unroll
    for (int j = 0; j < 4; j++) {
        const uint32_t x0 = __shfl_sync(FULL, vpair, 4 * j + src);
        const uint32_t x1 = __shfl_sync(FULL, vpair, 4 * j + 2 + src);
        uint32_t b0 = x0, b1 = x1;
        if (STATS && (lane & 4)) b0 = b1 = 0x3f803f80u;
        uint32_t f[4];
        ldsm4t(f, a0 + j * 1024);
        mma16816(c[0], f, b0, b1);
        ldsm4t(f, (a0 ^ 32u) + j * 1024);
        mma16816(c[1], f, b0, b1);
        if (STATS) mma16816(st, x0, x0, x1, x1, b0, b1);
    }
}

__global__ void __launch_bounds__(NW * 32, 1)
decode_kernel(const __grid_constant__ Params p) {
    extern __shared__ __align__(1024) unsigned char smem_raw[];
    const uint32_t smem = (uint32_t)__cvta_generic_to_shared(smem_raw);
    int lane = lane_id();
    const int w = __shfl_sync(FULL, threadIdx.x >> 5, 0);
    const int cta = blockIdx.x, h = cta >> 4;
    const uint32_t wslots = smem + w * (NSLOT * TILE);
    const uint32_t wbars = smem + OFF_BAR + w * (NSLOT * 8);
    TSTAMP(0);
    if (lane < NSLOT) {
        asm volatile("mbarrier.init.shared::cta.b64 [%0], 1;" :: "r"(wbars + lane * 8) : "memory");
        asm volatile("fence.proxy.async.shared::cta;" ::: "memory");
    }
    __syncwarp();
    refill(p, 16 | (M_WQA << 6), wslots, wbars, w);
#pragma unroll
    for (int i = 1; i < NFIRST; i++) refill(p, (i << 16) | 16 | (((i - 1) & 1) << 6) | (((i - 1) >> 1) << 9), wslots, wbars, w);
    uint32_t xp = reinterpret_cast<const uint32_t*>(p.x)[32 * w + 2 * (lane & 15) + (lane >> 4)];
    TSTAMP(1);
    int c = 0;

    uint32_t rk[NRF][32], rv[NRF][32];

#pragma unroll 1
    for (int layer = 0; layer < 4; layer++) {
        const uint32_t tag = (layer + 1) & 3;
        {
            const uint32_t e = p.steps[c++];
            wait_step(wbars, e);
            const int g = lane >> 2, t = lane & 3;
            float cc[2][4], st[4];
            gemv_tile<true>(slot_addr(wslots, e), xp, cc, st, lane);
            const float v0 = t == 0 ? cc[0][0] : (t == 1 ? cc[0][2] : (t == 2 ? cc[1][0] : cc[1][2]));
            const float v1 = t == 0 ? cc[0][1] : (t == 1 ? cc[0][3] : (t == 2 ? cc[1][1] : cc[1][3]));
            sts2(smem + OFF_RED + w * 256 + (8 * t + g) * 8, v0, v1);
            if (lane == 0) sts2(smem + OFF_ST + w * 8, st[0], st[1]);
            __syncthreads();
            if (w == 0 && lane < 16) {
                float u[8][4], z[16];
#pragma unroll
                for (int i = 0; i < 4; i++) lds4(z + 4 * i, smem + OFF_ST + 16 * i);
#pragma unroll
                for (int i = 0; i < 8; i++) lds4(u[i], smem + OFF_RED + i * 256 + lane * 16);
                const float sq = ((z[0] + z[2]) + (z[4] + z[6])) + ((z[8] + z[10]) + (z[12] + z[14]));
                const float su = ((z[1] + z[3]) + (z[5] + z[7])) + ((z[9] + z[11]) + (z[13] + z[15]));
                const float mean = su * (1.f / 512.f);
                const float rstd = rsq(fmaxf(fmaf(-mean, mean, sq * (1.f / 512.f)), 0.f) + 1e-5f);
                float r[4];
#pragma unroll
                for (int k = 0; k < 4; k++) r[k] = ((u[0][k] + u[1][k]) + (u[2][k] + u[3][k])) + ((u[4][k] + u[5][k]) + (u[6][k] + u[7][k]));
                st_rlx8(&p.xc->q[cta][2 * lane],
                        tagged(fmaf(-mean, r[1], r[0]) * rstd, tag), __float_as_uint(fmaf(-mean, r[3], r[2]) * rstd));
            }
            TSTAMP(2 + layer * 8);
            __syncthreads();
            if (layer == 0) {
#pragma unroll 1
                for (int i = NFIRST; i < NFIRST + p.nsecond; i++) refill(p, (i << 16) | 16 | (((i - 1) & 1) << 6) | (((i - 1) >> 1) << 9), wslots, wbars, w);
            }
            refill(p, e, wslots, wbars, w);
        }
        Attn a;
        {
            const float* src = &p.xc->q[h * 16 + 2 * w][2 * lane];
            uint32_t v0, v1;
            int it = 0;
            do { ld_rlx8(v0, v1, src); } while (!__all_sync(FULL, ((v0 ^ tag) & 3u) == 0u) && ++it < SPIN_LIMIT);
            sts(smem + OFF_RED + ((lane >> 4) * 32 + 4 * ((w >> 1) + 4 * (w & 1)) + (lane & 3)) * 16 + (lane & 12),
                __uint_as_float(pack_bf16(__uint_as_float(v0), __uint_as_float(v1))));
            __syncthreads();
            lds4(reinterpret_cast<float*>(a.qf), smem + OFF_RED + lane * 16);
            lds4(reinterpret_cast<float*>(a.qf + 4), smem + OFF_RED + 512 + lane * 16);
        }
        TSTAMP(3 + layer * 8);
#pragma unroll
        for (int i = 0; i < 16; i++) a.o[i] = 0.f;
        a.n0 = a.n1 = INFINITY;
        a.l0 = a.l1 = 0.f;
        const uint32_t offk = (((lane >> 3) & 1) * 8 + (lane & 7)) * 128 + ((((lane >> 4) & 1) ^ (lane & 7)) << 4);
        const uint32_t offv = (((lane >> 4) & 1) * 8 + (lane & 7)) * 128 + ((((lane >> 3) & 1) ^ (lane & 7)) << 4);
        uint32_t ev;
#pragma unroll 1
        for (;;) {
            if (p.steps[c] & STEP_RF) {
#pragma unroll
                for (int r = 0; r < NRF; r++) {
                    float sc[8];
                    uint32_t b[4];
                    if (layer == 0) {
                        const uint32_t e = p.steps[c++];
                        wait_step(wbars, e);
                        const uint32_t base = slot_addr(wslots, e) + offk;
#pragma unroll
                        for (int j = 0; j < 4; j++) {
                            ldsm4(&rk[r][8 * j], base ^ (j << 5));
                            ldsm4(&rk[r][8 * j + 4], (base ^ (j << 5)) + 2048);
                        }
                        asm volatile("" :: "r"(rk[r][31]), "r"(rk[r][27]) : "memory");
                        refill(p, e, wslots, wbars, w);
                    }
#pragma unroll
                    for (int i = 0; i < 8; i++) sc[i] = 0.f;
#pragma unroll
                    for (int j = 0; j < 4; j++) {
                        mma16816(sc, &rk[r][8 * j], a.qf[2 * j], a.qf[2 * j + 1]);
                        mma16816(sc + 4, &rk[r][8 * j + 4], a.qf[2 * j], a.qf[2 * j + 1]);
                    }
                    softmax_step(a, sc, b);
                    if (layer == 0) {
                        const uint32_t e = p.steps[c++];
                        wait_step(wbars, e);
                        const uint32_t base = slot_addr(wslots, e) + offv;
#pragma unroll
                        for (int j = 0; j < 4; j++) {
                            ldsm4t(&rv[r][8 * j], base ^ (j << 5));
                            ldsm4t(&rv[r][8 * j + 4], (base ^ (j << 5)) + 2048);
                        }
                        asm volatile("" :: "r"(rv[r][31]), "r"(rv[r][27]) : "memory");
                        refill(p, e, wslots, wbars, w);
                    }
#pragma unroll
                    for (int j = 0; j < 4; j++) {
                        mma16816(a.o + 4 * j, &rv[r][8 * j], b[0], b[1]);
                        mma16816(a.o + 4 * j, &rv[r][8 * j + 4], b[2], b[3]);
                    }
                }
            }
            float sc[8];
            uint32_t b[4];
            const uint32_t ek = p.steps[c++];
            ev = p.steps[c++];
            {
                wait_step(wbars, ek);
                const uint32_t base = slot_addr(wslots, ek) + offk;
#pragma unroll
                for (int i = 0; i < 8; i++) sc[i] = 0.f;
#pragma unroll
                for (int j = 0; j < 4; j++) {
                    uint32_t f[8];
                    ldsm4(f, base ^ (j << 5));
                    ldsm4(f + 4, (base ^ (j << 5)) + 2048);
                    mma16816(sc, f, a.qf[2 * j], a.qf[2 * j + 1]);
                    mma16816(sc + 4, f + 4, a.qf[2 * j], a.qf[2 * j + 1]);
                }
                refill(p, ek, wslots, wbars, w);
            }
            softmax_step(a, sc, b);
            {
                wait_step(wbars, ev);
                const uint32_t base = slot_addr(wslots, ev) + offv;
#pragma unroll
                for (int j = 0; j < 4; j++) {
                    uint32_t f[8];
                    ldsm4t(f, base ^ (j << 5));
                    ldsm4t(f + 4, (base ^ (j << 5)) + 2048);
                    mma16816(a.o + 4 * j, f, b[0], b[1]);
                    mma16816(a.o + 4 * j, f + 4, b[2], b[3]);
                }
            }
            if (ev & STEP_LAST) break;
            refill(p, ev, wslots, wbars, w);
        }
        lane = lane_id();
        const int g = lane >> 2, t = lane & 3, half = lane >> 4, c16 = lane & 15;
        TSTAMP(4 + layer * 8);
        {
            a.l0 += __shfl_xor_sync(FULL, a.l0, 8);
            a.l1 += __shfl_xor_sync(FULL, a.l1, 8);
            a.l0 += __shfl_xor_sync(FULL, a.l0, 16);
            a.l1 += __shfl_xor_sync(FULL, a.l1, 16);
            const uint32_t o0 = slot_addr(wslots, ev) + ((4 * (t & 1) + (t >> 1)) * 96 + 8 * t + g) * 4;
#pragma unroll
            for (int i = 0; i < 4; i++) {
                sts(o0 + i * 64, a.o[4 * i]);
                sts(o0 + i * 64 + 192 * 4, a.o[4 * i + 1]);
                sts(o0 + i * 64 + 32, a.o[4 * i + 2]);
                sts(o0 + i * 64 + 192 * 4 + 32, a.o[4 * i + 3]);
            }
            if (lane < 2) {
                sts2(smem + OFF_ML + (2 * lane) * 64 + w * 8, -a.n0, a.l0);
                sts2(smem + OFF_ML + (2 * lane + 1) * 64 + w * 8, -a.n1, a.l1);
            }
            __syncthreads();
            float ml[16], u[4][4];
#pragma unroll
            for (int i = 0; i < 4; i++) lds4(ml + 4 * i, smem + OFF_ML + (w >> 1) * 64 + ((16 * i) ^ (half * 32)));
            const uint32_t ro = slot_addr(smem, ev) + half * (4 * NSLOT * TILE) + (w * 96 + 8 * ((w >> 2) + 2 * (w & 1)) + 4 * c16) * 4;
#pragma unroll
            for (int i = 0; i < 4; i++) lds4(u[i], ro + i * (NSLOT * TILE));
            const float M = fmaxf(fmaxf(fmaxf(ml[0], ml[2]), fmaxf(ml[4], ml[6])), fmaxf(fmaxf(ml[8], ml[10]), fmaxf(ml[12], ml[14])));
            float f[4], r[4];
#pragma unroll
            for (int i = 0; i < 4; i++) f[i] = ex2(ml[2 * i] - M);
            float L = fmaf(f[0], ml[1], f[1] * ml[3]) + fmaf(f[2], ml[5], f[3] * ml[7]);
            L += __shfl_xor_sync(FULL, L, 16);
#pragma unroll
            for (int k = 0; k < 4; k++) {
                r[k] = fmaf(f[0], u[0][k], f[1] * u[1][k]) + fmaf(f[2], u[2][k], f[3] * u[3][k]);
                r[k] += __shfl_xor_sync(FULL, r[k], 16);
            }
            const float il = rcp(L);
            if (lane <= 16) st_rlx16(&p.xc->part[cta][w][4 * lane], tagged(half ? M + lg2(L) : r[0] * il, tag),
                                     __float_as_uint(r[1] * il), __float_as_uint(r[2] * il), __float_as_uint(r[3] * il));
            TSTAMP(5 + layer * 8);
            asm volatile("fence.proxy.async.shared::cta;" ::: "memory");
            __syncthreads();
            refill(p, ev, wslots, wbars, w);
        }
        {
            const uint32_t e = p.steps[c++];
            uint32_t v[8][4], su = ~tag;
            const float* src = &p.xc->part[h * 16 + half][w][4 * c16];
            const float* ssrc = &p.xc->part[h * 16 + c16][w][64];
#pragma unroll
            for (int j = 0; j < 8; j++) { v[j][0] = ~tag; v[j][1] = v[j][2] = v[j][3] = 0u; }
            int it = 0;
            bool ok;
            do {
                if ((su ^ tag) & 3u) su = ld_rlx(ssrc);
#pragma unroll
                for (int j = 0; j < 8; j++)
                    if ((v[j][0] ^ tag) & 3u) ld_rlx16(v[j], src + j * (2 * NW * 96));
                uint32_t bad = su ^ tag;
#pragma unroll
                for (int j = 0; j < 8; j++) bad |= v[j][0] ^ tag;
                ok = (bad & 3u) == 0u;
            } while (!__all_sync(FULL, ok) && ++it < SPIN_LIMIT);
            TSTAMP(6 + layer * 8);
            const int key = (int)su ^ (((int)su >> 31) & 0x7fffffff);
            const int kmax = __reduce_max_sync(FULL, key);
            const float M = __int_as_float(kmax ^ ((kmax >> 31) & 0x7fffffff));
            const float f = ex2(__uint_as_float(su) - M);
            float r[4] = {0.f, 0.f, 0.f, 0.f}, L = 0.f;
#pragma unroll
            for (int j = 0; j < 8; j++) {
                const float fj = __shfl_sync(FULL, f, 2 * j + half);
                L += fj;
#pragma unroll
                for (int k = 0; k < 4; k++) r[k] = fmaf(fj, __uint_as_float(v[j][k]), r[k]);
            }
            L += __shfl_xor_sync(FULL, L, 16);
            const float y0 = (half ? r[2] : r[0]) + __shfl_xor_sync(FULL, half ? r[0] : r[2], 16);
            const float y1 = (half ? r[3] : r[1]) + __shfl_xor_sync(FULL, half ? r[1] : r[3], 16);
            const float il = rcp(L);
            wait_step(wbars, e);
            float cc[2][4];
            gemv_tile<false>(slot_addr(wslots, e), pack_bf16(y0 * il, y1 * il), cc, nullptr, lane);
            sts(smem + OFF_RED + w * 128 + (8 * t + g) * 4, t == 0 ? cc[0][0] : (t == 1 ? cc[0][2] : (t == 2 ? cc[1][0] : cc[1][2])));
            __syncthreads();
            if (w == 0 && lane < 8) {
                float u[8][4];
#pragma unroll
                for (int i = 0; i < 8; i++) lds4(u[i], smem + OFF_RED + i * 128 + lane * 16);
#pragma unroll
                for (int k = 0; k < 4; k++) r[k] = ((u[0][k] + u[1][k]) + (u[2][k] + u[3][k])) + ((u[4][k] + u[5][k]) + (u[6][k] + u[7][k]));
                st_rlx16(&p.xc->x[layer & 1][cta][4 * lane], tagged(r[0], tag), __float_as_uint(r[1]), __float_as_uint(r[2]), __float_as_uint(r[3]));
            }
            TSTAMP(7 + layer * 8);
            if (layer == 3 && cta != 0) return;
            __syncthreads();
            refill(p, e, wslots, wbars, w);
        }
        {
            uint32_t v[4][4];
            const float* src = &p.xc->x[layer & 1][16 * half + 2 * w][4 * c16];
#pragma unroll
            for (int j = 0; j < 4; j++) { v[j][0] = ~tag; v[j][1] = v[j][2] = v[j][3] = 0u; }
            int it = 0;
            bool ok;
            do {
#pragma unroll
                for (int j = 0; j < 4; j++)
                    if ((v[j][0] ^ tag) & 3u) ld_rlx16(v[j], src + j * 1024);
                ok = (((v[0][0] ^ tag) | (v[1][0] ^ tag) | (v[2][0] ^ tag) | (v[3][0] ^ tag)) & 3u) == 0u;
            } while (!__all_sync(FULL, ok) && ++it < SPIN_LIMIT);
            float r[4];
#pragma unroll
            for (int k = 0; k < 4; k++)
                r[k] = (__uint_as_float(v[0][k]) + __uint_as_float(v[1][k])) + (__uint_as_float(v[2][k]) + __uint_as_float(v[3][k]));
            const float y0 = (half ? r[2] : r[0]) + __shfl_xor_sync(FULL, half ? r[0] : r[2], 16);
            const float y1 = (half ? r[3] : r[1]) + __shfl_xor_sync(FULL, half ? r[1] : r[3], 16);
            const uint32_t yb = pack_bf16(y0, y1);
            xp = pack_bf16(bf_lo(xp) + bf_lo(yb), bf_hi(xp) + bf_hi(yb));
        }
        TSTAMP(8 + layer * 8);
    }
    reinterpret_cast<uint32_t*>(p.out)[32 * w + 2 * (lane & 15) + (lane >> 4)] = xp;
}

typedef CUresult (*EncodeFn)(CUtensorMap*, CUtensorMapDataType, cuuint32_t, void*, const cuuint64_t*, const cuuint64_t*,
                             const cuuint32_t*, const cuuint32_t*, CUtensorMapInterleave, CUtensorMapSwizzle,
                             CUtensorMapL2promotion, CUtensorMapFloatOOBfill);

void encode5d(EncodeFn enc, CUtensorMap* m, const void* ptr, uint32_t cols, uint32_t rows, uint32_t nchunk,
              uint64_t srow, uint64_t schunk, uint64_t ss, uint64_t sh, CUtensorMapSwizzle sw, CUtensorMapL2promotion promo) {
    cuuint64_t dims[5] = {cols, rows, nchunk, 16, 8};
    cuuint64_t strides[4] = {srow, schunk, ss, sh};
    cuuint32_t box[5] = {cols, rows, 1, 1, 1};
    cuuint32_t es[5] = {1, 1, 1, 1, 1};
    CUresult r = enc(m, CU_TENSOR_MAP_DATA_TYPE_BFLOAT16, 5, const_cast<void*>(ptr), dims, strides, box, es,
        CU_TENSOR_MAP_INTERLEAVE_NONE, sw, promo, CU_TENSOR_MAP_FLOAT_OOB_FILL_NONE);
    (void)r;
}

struct Sched {
    int nkeep = 5;
    int nl2 = 11;
    int promoB = 0;
    int promoW = 0;
    int rfpos3 = 3;
    int nsecond = 1;
    int d1 = 2;
    int d3 = 4;
};

void build_schedule(Params& p, const Sched& sc) {
    struct Item { int map, tile, promote; };
    Item items[96];
    int n = 0;
    auto add = [&](int map, int tile, int promote) { items[n++] = Item{map, tile, promote}; };
    const int rf0 = (sc.nkeep + 1) / 2;
    add(M_WQA, 0, 0);
    for (int u = 0; u < 32; u++) add(u & 1, u >> 1, u >= 32 - sc.nl2);
    add(M_WOA, 0, sc.promoW & 1);
    add(M_WQB, 0, sc.promoB & 1);
    for (int u = 0; u < 4; u++) add(M_KB + (u & 1), u >> 1, (sc.promoB >> (1 + u)) & 1);
    add(M_WOB, 0, (sc.promoB >> 5) & 1);
    add(M_WQA, 0, 0);
    if (sc.nkeep & 1) add(1, sc.nkeep >> 1, 0);
    const int lo = rf0 + NRF, hi = 15;
    const int l2first = (32 - sc.nl2) / 2;
    const int nd = l2first - lo, nh = 16 - l2first;
    int di = 0, hi_i = 0;
    while (di < nd || hi_i < nh) {
        const bool takeD = hi_i >= nh || (di < nd && di * nh <= hi_i * nd);
        const int pr = takeD ? lo + di++ : hi - hi_i++;
        add(0, pr, 0); add(1, pr, 0);
    }
    add(M_WOA, 0, 0); add(M_WQB, 0, 0);
    for (int u = 0; u < 4; u++) add(M_KB + (u & 1), u >> 1, 0);
    add(M_WOB, 0, 0);
    const int n0 = NFIRST + sc.nsecond;
    int fifo[16], nf = 0, kept[16], nk = 0, fre[16], nfree = 0, par[NSLOT] = {0}, ic = n0, c = 0, skip = 0;
    for (int i = 0; i < n0; i++) fifo[nf++] = i;
    for (int i = NSLOT - 1; i >= n0; i--) fre[nfree++] = i;
    for (int i = 0; i < 80; i++) p.steps[i] = 0;
    auto step = [&](bool keep, int depth) {
        const int slot = fifo[0];
        for (int i = 1; i < nf; i++) fifo[i - 1] = fifo[i];
        nf--;
        if (skip > 0) skip--;
        uint32_t e = slot | (par[slot] << 3);
        if (keep) kept[nk++] = slot; else { par[slot] ^= 1; fre[nfree++] = slot; }
        if (ic < n && nfree > 0 && nf - skip < depth) {
            const Item& it = items[ic++];
            const int dst = fre[--nfree];
            e |= 16 | (it.promote << 5) | (it.map << 6) | (it.tile << 9) | (dst << 16);
            fifo[nf++] = dst;
        }
        p.steps[c++] = e;
    };
    step(false, 7);
    for (int u = 0; u < 32; u++) step(u < sc.nkeep, u < 2 ? 7 : sc.d1);
    p.steps[1 + 2 * rf0] |= STEP_RF;
    p.steps[c - 1] |= STEP_LAST;
    step(false, sc.d1);
    for (int u = 0; u < 5; u++) step(false, sc.d1);
    p.steps[c - 1] |= STEP_LAST;
    step(false, sc.d1);
    step(false, sc.d1);
    for (int i = nf - 1; i >= 0; i--) fifo[i + nk] = fifo[i];
    for (int i = 0; i < nk; i++) fifo[i] = kept[i];
    nf += nk; skip = nk;
    const int c3 = c;
    for (int u = 0; u < 32 - 2 * NRF; u++) step(false, sc.d3);
    p.steps[c3 + 2 * sc.rfpos3] |= STEP_RF;
    p.steps[c - 1] |= STEP_LAST;
    step(false, sc.d3);
    for (int u = 0; u < 5; u++) step(false, sc.d3);
    p.steps[c - 1] |= STEP_LAST;
    step(false, sc.d3);
    p.nsecond = sc.nsecond;
}

Sched g_sched;

}

extern "C" void kernel_launch(void* const* d_in, const int* in_sizes, int n_in, void* d_out, int out_size) {
    (void)in_sizes; (void)n_in; (void)out_size;
    void* fn = nullptr;
    cudaDriverEntryPointQueryResult qr;
    cudaGetDriverEntryPoint("cuTensorMapEncodeTiled", &fn, cudaEnableDefault, &qr);
    EncodeFn enc = (EncodeFn)fn;
    Params p;
    const CUtensorMapL2promotion pk = CU_TENSOR_MAP_L2_PROMOTION_L2_256B, pw = CU_TENSOR_MAP_L2_PROMOTION_NONE;
    const size_t win = (size_t)28672 * 256;
    encode5d(enc, &p.maps[M_KA], d_in[1], 64, 32, 128, 128, 4096, 512 << 10, 8 << 20, CU_TENSOR_MAP_SWIZZLE_128B, pk);
    encode5d(enc, &p.maps[M_VA], d_in[2], 64, 32, 128, 128, 4096, 512 << 10, 8 << 20, CU_TENSOR_MAP_SWIZZLE_128B, pk);
    encode5d(enc, &p.maps[M_KB], (const char*)d_in[6] + win, 64, 32, 16, 128, 4096, 64 << 10, 8 << 20, CU_TENSOR_MAP_SWIZZLE_128B, pk);
    encode5d(enc, &p.maps[M_VB], (const char*)d_in[7] + win, 64, 32, 16, 128, 4096, 64 << 10, 8 << 20, CU_TENSOR_MAP_SWIZZLE_128B, pk);
    encode5d(enc, &p.maps[M_WQA], d_in[3], 32, 64, 8, 8192, 64 * 8192, 64, 1024, CU_TENSOR_MAP_SWIZZLE_64B, pw);
    encode5d(enc, &p.maps[M_WQB], d_in[8], 32, 64, 8, 8192, 64 * 8192, 64, 1024, CU_TENSOR_MAP_SWIZZLE_64B, pw);
    encode5d(enc, &p.maps[M_WOA], d_in[4], 32, 64, 8, 1024, 64 << 10, 64, 512 << 10, CU_TENSOR_MAP_SWIZZLE_64B, pw);
    encode5d(enc, &p.maps[M_WOB], d_in[9], 32, 64, 8, 1024, 64 << 10, 64, 512 << 10, CU_TENSOR_MAP_SWIZZLE_64B, pw);
    void* xc = nullptr;
    cudaGetSymbolAddress(&xc, g_xchg);
    p.xc = (Xchg*)xc;
    p.x = (const __nv_bfloat16*)d_in[0];
    p.out = (__nv_bfloat16*)d_out;
    build_schedule(p, g_sched);
    cudaFuncSetAttribute(decode_kernel, cudaFuncAttributeMaxDynamicSharedMemorySize, SMEM_BYTES);
    decode_kernel<<<NCTA, NW * 32, SMEM_BYTES, cudaStreamPerThread>>>(p);
}
```

```cpp
#include <cuda_runtime.h>
#include <cuda_bf16.h>
#include <cuda.h>
#include <stdint.h>

namespace {

constexpr int NCTA  = 128;
constexpr int NW    = 8;
constexpr int NSLOT = 7;
constexpr int TILE  = 4096;
constexpr int NFIRST = 3;
#define NRF 3

constexpr int OFF_BAR = NW * NSLOT * TILE;
constexpr int OFF_RED = OFF_BAR + 512;
constexpr int OFF_ST  = OFF_RED + 2048;
constexpr int OFF_ML  = OFF_ST + 64;
constexpr int SMEM_BYTES = OFF_ML + 256;

constexpr uint64_t POL_EVICT_FIRST = 0x12F0000000000000ull;
constexpr int SPIN_LIMIT = 1 << 20;
constexpr unsigned FULL = 0xffffffffu;

enum { M_KA = 0, M_VA = 1, M_KB = 2, M_VB = 3, M_WQA = 4, M_WQB = 5, M_WOA = 6, M_WOB = 7 };

constexpr uint32_t STEP_LAST = 1u << 13, STEP_RF = 1u << 20;
constexpr int NSTEP = 112;
struct Xchg {
    float q[NCTA][32];
    float part[NCTA][NW][96];
    float x[2][NCTA][32];
};
struct __align__(64) Params {
    CUtensorMap maps[8];
    const __nv_bfloat16* x;
    __nv_bfloat16* out;
    Xchg* xc;
    int nap;
    int first[4], last[4];
    uint32_t steps[NSTEP];
};
__device__ __align__(128) Xchg g_xchg;
#define TSTAMP(i)

__device__ __forceinline__ int lane_id() { int l; asm volatile("mov.u32 %0, %%laneid;" : "=r"(l)); return l; }
__device__ __forceinline__ bool mbar_try(uint32_t bar, uint32_t parity) {
    uint32_t ok;
    asm volatile("{\n.reg .pred p;\nmbarrier.try_wait.parity.shared::cta.b64 p, [%1], %2;\nselp.u32 %0, 1, 0, p;\n}"
                 : "=r"(ok) : "r"(bar), "r"(parity) : "memory");
    return __all_sync(0xffffffffu, ok);
}
__device__ __forceinline__ void mbar_wait(uint32_t bar, uint32_t parity) {
    if (!mbar_try(bar, parity)) {
        int n = 0;
        while (!mbar_try(bar, parity) && ++n < (1 << 17)) {}
    }
}
__device__ __forceinline__ void ldsm4(uint32_t* r, uint32_t a) {
    asm volatile("ldmatrix.sync.aligned.m8n8.x4.shared.b16 {%0,%1,%2,%3}, [%4];"
                 : "=r"(r[0]), "=r"(r[1]), "=r"(r[2]), "=r"(r[3]) : "r"(a) : "memory");
}
__device__ __forceinline__ void ldsm4t(uint32_t* r, uint32_t a) {
    asm volatile("ldmatrix.sync.aligned.m8n8.x4.trans.shared.b16 {%0,%1,%2,%3}, [%4];"
                 : "=r"(r[0]), "=r"(r[1]), "=r"(r[2]), "=r"(r[3]) : "r"(a) : "memory");
}
__device__ __forceinline__ void mma16816(float* c, uint32_t a0, uint32_t a1, uint32_t a2, uint32_t a3, uint32_t b0, uint32_t b1) {
    asm volatile("mma.sync.aligned.m16n8k16.row.col.f32.bf16.bf16.f32 {%0,%1,%2,%3}, {%4,%5,%6,%7}, {%8,%9}, {%0,%1,%2,%3};"
                 : "+f"(c[0]), "+f"(c[1]), "+f"(c[2]), "+f"(c[3])
                 : "r"(a0), "r"(a1), "r"(a2), "r"(a3), "r"(b0), "r"(b1));
}
__device__ __forceinline__ void mma16816(float* c, const uint32_t* a, uint32_t b0, uint32_t b1) { mma16816(c, a[0], a[1], a[2], a[3], b0, b1); }
__device__ __forceinline__ uint32_t movm(uint32_t a) {
    uint32_t d;
    asm volatile("movmatrix.sync.aligned.m8n8.trans.b16 %0, %1;" : "=r"(d) : "r"(a));
    return d;
}
__device__ __forceinline__ uint32_t pack_bf16(float lo, float hi) {
    uint32_t d;
    asm("cvt.rn.bf16x2.f32 %0, %1, %2;" : "=r"(d) : "f"(hi), "f"(lo));
    return d;
}
__device__ __forceinline__ float bf_lo(uint32_t v) { return __uint_as_float(v << 16); }
__device__ __forceinline__ float bf_hi(uint32_t v) { return __uint_as_float(v & 0xffff0000u); }
__device__ __forceinline__ float ex2(float v) { float d; asm("ex2.approx.ftz.f32 %0, %1;" : "=f"(d) : "f"(v)); return d; }
__device__ __forceinline__ float rcp(float v) { float d; asm("rcp.approx.ftz.f32 %0, %1;" : "=f"(d) : "f"(v)); return d; }
__device__ __forceinline__ float rsq(float v) { float d; asm("rsqrt.approx.ftz.f32 %0, %1;" : "=f"(d) : "f"(v)); return d; }
__device__ __forceinline__ uint32_t tagged(float v, uint32_t tag) { return (__float_as_uint(v) & ~3u) | tag; }

__device__ __forceinline__ void st_rlx8(void* p, uint32_t a, uint32_t b) {
    asm volatile("{\n.reg .b64 l;\nmov.b64 l, {%1,%2};\nst.relaxed.gpu.global.b64 [%0], l;\n}" :: "l"(p), "r"(a), "r"(b) : "memory");
}
__device__ __forceinline__ void ld_rlx8(uint32_t& a, uint32_t& b, const void* p) {
    asm volatile("{\n.reg .b64 l;\nld.relaxed.gpu.global.b64 l, [%2];\nmov.b64 {%0,%1}, l;\n}" : "=r"(a), "=r"(b) : "l"(p) : "memory");
}
__device__ __forceinline__ void st_rlx16(void* p, uint32_t a, uint32_t b, uint32_t c, uint32_t d) {
    asm volatile("{\n.reg .b64 l, h;\n.reg .b128 v;\nmov.b64 l, {%1,%2};\nmov.b64 h, {%3,%4};\nmov.b128 v, {l,h};\n"
                 "st.relaxed.gpu.global.b128 [%0], v;\n}" :: "l"(p), "r"(a), "r"(b), "r"(c), "r"(d) : "memory");
}
__device__ __forceinline__ void ld_rlx16(uint32_t* r, const void* p) {
    asm volatile("{\n.reg .b64 l, h;\n.reg .b128 v;\nld.relaxed.gpu.global.b128 v, [%4];\nmov.b128 {l,h}, v;\n"
                 "mov.b64 {%0,%1}, l;\nmov.b64 {%2,%3}, h;\n}" : "=r"(r[0]), "=r"(r[1]), "=r"(r[2]), "=r"(r[3]) : "l"(p) : "memory");
}
__device__ __forceinline__ void sts(uint32_t a, float v) { asm volatile("st.shared.f32 [%0], %1;" :: "r"(a), "f"(v) : "memory"); }
__device__ __forceinline__ void sts2(uint32_t a, float x, float y) { asm volatile("st.shared.v2.f32 [%0], {%1,%2};" :: "r"(a), "f"(x), "f"(y) : "memory"); }
__device__ __forceinline__ void lds4(float* v, uint32_t a) { asm volatile("ld.shared.v4.f32 {%0,%1,%2,%3}, [%4];" : "=f"(v[0]), "=f"(v[1]), "=f"(v[2]), "=f"(v[3]) : "r"(a) : "memory"); }

constexpr float SCALE_LOG2E = 0.08838834764831845f * 1.4426950408889634f;
constexpr float MAX_SLACK = 8.f;

__device__ __forceinline__ uint32_t slot_addr(uint32_t wslots, uint32_t e) { return wslots + (e & 7u) * TILE; }
__device__ __forceinline__ uint32_t slot_bar(uint32_t wbars, uint32_t e) { return wbars + (e & 7u) * 8; }
__device__ __forceinline__ void wait_step(uint32_t wbars, uint32_t e) { mbar_wait(slot_bar(wbars, e), (e >> 3) & 1u); }
__device__ __forceinline__ void refill(const Params& p, uint32_t e, uint32_t wslots, uint32_t wbars, int w) {
    const unsigned char* m = reinterpret_cast<const unsigned char*>(&p.maps[0]) + ((e << 1) & 0x380u);
    const int c2 = w + ((e >> 6) & 0x78u), c3 = blockIdx.x & 15, c4 = blockIdx.x >> 4;
    asm volatile("{\n.reg .pred p, q;\n"
                 "elect.sync _|p, 0xffffffff;\n"
                 "setp.ne.and.u32 q, %9, 0, p;\n"
                 "setp.ne.and.u32 p, %8, 0, p;\n"
                 "@p mbarrier.arrive.expect_tx.shared::cta.b64 _, [%6], 4096;\n"
                 "@p cp.async.bulk.tensor.5d.shared::cluster.global.mbarrier::complete_tx::bytes.L2::cache_hint [%0], [%1, {%2,%2,%3,%4,%5}], [%6], %7;\n"
                 "@q cp.async.bulk.prefetch.tensor.5d.L2.global.tile [%1, {%2,%2,%3,%4,%5}];\n"
                 "}"
                 :: "r"(slot_addr(wslots, e >> 16)), "l"(m), "r"(0), "r"(c2), "r"(c3), "r"(c4), "r"(slot_bar(wbars, e >> 16)), "l"(POL_EVICT_FIRST),
                    "r"(e & 16u), "r"(e & 32u) : "memory");
}

__device__ __forceinline__ void refill_if(const Params& p, uint32_t e, uint32_t wslots, uint32_t wbars, int w) {
    if (e & 48u) refill(p, e, wslots, wbars, w);
}
template <class T> __device__ __forceinline__ T* pin(T* q) { asm volatile("" : "+l"(q)); return q; }
__device__ __forceinline__ uint32_t pin(uint32_t v) { asm volatile("" : "+r"(v)); return v; }
__device__ __forceinline__ float selp(float a, float b, bool c) {
    float d;
    asm("{\n.reg .pred p;\nsetp.ne.u32 p, %3, 0;\nselp.f32 %0, %1, %2, p;\n}" : "=f"(d) : "f"(a), "f"(b), "r"((uint32_t)c));
    return d;
}

constexpr uint32_t SWAP = 0x90;
struct Attn {
    uint32_t qf[8];
    float o[16];
    float n0, n1;
    float l0, l1;
    uint32_t mv;
};
__device__ __forceinline__ void load_k(uint32_t* f, uint32_t base) {
#pragma unroll
    for (int j = 0; j < 4; j++) {
        ldsm4(f + 8 * j, base ^ (j << 5));
        ldsm4(f + 8 * j + 4, (base ^ (j << 5) ^ SWAP) + 2048);
    }
}
__device__ __forceinline__ void load_v(uint32_t* f, uint32_t base) {
#pragma unroll
    for (int j = 0; j < 4; j++) ldsm4t(f + 8 * j, base ^ (j << 5));
#pragma unroll
    for (int j = 0; j < 4; j++) ldsm4t(f + 8 * j + 4, (base ^ (j << 5) ^ SWAP) + 2048);
}
__device__ __forceinline__ void qk(const Attn& a, const uint32_t* f, float* s) {
    float c[8];
#pragma unroll
    for (int i = 0; i < 8; i++) c[i] = 0.f;
#pragma unroll
    for (int j = 0; j < 4; j++) {
        mma16816(c, f + 8 * j, a.qf[2 * j], a.qf[2 * j + 1]);
        mma16816(c + 4, f + 8 * j + 4, a.qf[2 * j], a.qf[2 * j + 1]);
    }
#pragma unroll
    for (int i = 0; i < 4; i++) s[i] = __uint_as_float((__float_as_uint(c[i]) & a.mv) | (__float_as_uint(c[i + 4]) & ~a.mv));
}
__device__ __forceinline__ void pv(Attn& a, const uint32_t* f, const uint32_t* b) {
#pragma unroll
    for (int j = 0; j < 4; j++) mma16816(a.o + 4 * j, f + 8 * j, b[0], b[1]);
#pragma unroll
    for (int j = 0; j < 4; j++) mma16816(a.o + 4 * j, f + 8 * j + 4, b[2], b[3]);
}
__device__ __forceinline__ void probs(Attn& a, float* y, uint32_t* b) {
#pragma unroll
    for (int i = 0; i < 4; i++) y[i] = ex2(y[i]);
    const uint32_t p0 = pack_bf16(y[0], y[1]), p1 = pack_bf16(y[2], y[3]);
    b[0] = movm(p0 & a.mv); b[1] = movm(p1 & a.mv);
    b[2] = movm(p0 & ~a.mv); b[3] = movm(p1 & ~a.mv);
    a.l0 += y[0] + y[2];
    a.l1 += y[1] + y[3];
    asm volatile("" : "+f"(a.l0), "+f"(a.l1));
}
__device__ __forceinline__ void softmax_step(Attn& a, float* s, uint32_t* b) {
    float y[4];
#pragma unroll
    for (int i = 0; i < 4; i++) s[i] += __shfl_xor_sync(FULL, s[i], 6);
#pragma unroll
    for (int i = 0; i < 4; i++) y[i] = fmaf(s[i], SCALE_LOG2E, (i & 1) ? a.n1 : a.n0);
    if (__any_sync(FULL, fmaxf(fmaxf(y[0], y[1]), fmaxf(y[2], y[3])) > MAX_SLACK)) {
        float t0 = fmaxf(s[0], s[2]), t1 = fmaxf(s[1], s[3]);
#pragma unroll
        for (int d = 4; d <= 16; d <<= 1) {
            t0 = fmaxf(t0, __shfl_xor_sync(FULL, t0, d));
            t1 = fmaxf(t1, __shfl_xor_sync(FULL, t1, d));
        }
        t0 = fminf(-SCALE_LOG2E * t0, a.n0); t1 = fminf(-SCALE_LOG2E * t1, a.n1);
        const float r0 = ex2(t0 - a.n0), r1 = ex2(t1 - a.n1);
        a.n0 = t0; a.n1 = t1;
        a.l0 *= r0; a.l1 *= r1;
#pragma unroll
        for (int i = 0; i < 16; i += 2) { a.o[i] *= r0; a.o[i + 1] *= r1; }
#pragma unroll
        for (int i = 0; i < 4; i++) y[i] = fmaf(s[i], SCALE_LOG2E, (i & 1) ? a.n1 : a.n0);
    }
    probs(a, y, b);
}

__device__ __forceinline__ uint32_t add_residual(uint32_t xp, const uint32_t (*v)[4], bool half) {
    float r[4];
#pragma unroll
    for (int k = 0; k < 4; k++)
        r[k] = (__uint_as_float(v[0][k]) + __uint_as_float(v[1][k])) + (__uint_as_float(v[2][k]) + __uint_as_float(v[3][k]));
    const float y0 = selp(r[2], r[0], half) + __shfl_xor_sync(FULL, selp(r[0], r[2], half), 16);
    const float y1 = selp(r[3], r[1], half) + __shfl_xor_sync(FULL, selp(r[1], r[3], half), 16);
    const uint32_t yb = pack_bf16(y0, y1);
    return pack_bf16(bf_lo(xp) + bf_lo(yb), bf_hi(xp) + bf_hi(yb));
}

__device__ __forceinline__ void gemv_load(uint32_t (*f)[4], uint32_t tile, int lane) {
    const int mi = lane >> 3, r = lane & 7;
    const uint32_t a0 = tile + ((mi >> 1) * 8 + r) * 64 + (((mi & 1) ^ (r >> 1)) << 4);
#pragma unroll
    for (int j = 0; j < 4; j++) {
        ldsm4t(f[2 * j], a0 + j * 1024);
        ldsm4t(f[2 * j + 1], (a0 ^ 32u) + j * 1024);
    }
}
template <bool STATS>
__device__ __forceinline__ void gemv_mma(const uint32_t (*f)[4], uint32_t vpair, float& y0, float& y1, float* st, int lane) {
    const int src = ((lane >> 1) & 1) + 16 * (lane & 1);
    float c[4][4];
    uint32_t x[8];
#pragma unroll
    for (int j = 0; j < 8; j++) x[j] = __shfl_sync(FULL, vpair, 2 * j + src);
#pragma unroll
    for (int i = 0; i < 4; i++) { c[0][i] = c[1][i] = c[2][i] = c[3][i] = 0.f; if (STATS) st[i] = 0.f; }
#pragma unroll
    for (int j = 0; j < 4; j++) {
        uint32_t b0 = x[2 * j], b1 = x[2 * j + 1];
        if (STATS && (lane & 4)) b0 = b1 = 0x3f803f80u;
        mma16816(c[2 * (j & 1)], f[2 * j], b0, b1);
        mma16816(c[2 * (j & 1) + 1], f[2 * j + 1], b0, b1);
        if (STATS) mma16816(st, x[2 * j], x[2 * j], x[2 * j + 1], x[2 * j + 1], b0, b1);
    }
    const bool t1 = lane & 1, t2 = lane & 2;
    y0 = selp(selp(c[1][2] + c[3][2], c[1][0] + c[3][0], t1), selp(c[0][2] + c[2][2], c[0][0] + c[2][0], t1), t2);
    if (STATS) y1 = selp(selp(c[1][3] + c[3][3], c[1][1] + c[3][1], t1), selp(c[0][3] + c[2][3], c[0][1] + c[2][1], t1), t2);
}

__global__ void __launch_bounds__(NW * 32, 1)
decode_kernel(const __grid_constant__ Params p) {
    extern __shared__ __align__(1024) unsigned char smem_raw[];
    const uint32_t smem = (uint32_t)__cvta_generic_to_shared(smem_raw);
    int lane = lane_id();
    const int w = __shfl_sync(FULL, threadIdx.x >> 5, 0);
    const int cta = blockIdx.x, h = cta >> 4;
    const uint32_t wslots = smem + w * (NSLOT * TILE);
    const uint32_t wbars = smem + OFF_BAR + w * (NSLOT * 8);
    TSTAMP(0);
    if (lane < NSLOT) {
        asm volatile("mbarrier.init.shared::cta.b64 [%0], 1;" :: "r"(wbars + lane * 8) : "memory");
        asm volatile("fence.proxy.async.shared::cta;" ::: "memory");
    }
    __syncwarp();
    refill(p, 16 | (M_WQA << 6), wslots, wbars, w);
#pragma unroll
    for (int i = 1; i < NFIRST; i++) refill(p, (i << 16) | 16 | (((i - 1) & 1) << 6) | (((i - 1) >> 1) << 9), wslots, wbars, w);
    uint32_t xp = reinterpret_cast<const uint32_t*>(p.x)[32 * w + 2 * (lane & 15) + (lane >> 4)];
    TSTAMP(1);

    uint32_t rk[NRF][32], rv[NRF][32];

#pragma unroll 1
    for (int layer = 0; layer < 4; layer++) {
        const uint32_t tag = (layer + 1) & 3;
        int c = p.first[layer];
        Attn a;
        {
            const uint32_t e = p.steps[c];
            const int half = lane >> 4;
            const uint32_t ptag = layer & 3;
            const float* src = pin(&p.xc->x[(layer + 1) & 1][16 * half + 2 * w][4 * (lane & 15)]);
            uint32_t v[4][4], f[8][4];
            if (layer > 0) {
#pragma unroll
                for (int j = 0; j < 4; j++) ld_rlx16(v[j], src + j * 1024);
            } else {
#pragma unroll
                for (int j = 0; j < 4; j++) v[j][0] = v[j][1] = v[j][2] = v[j][3] = 0u;
            }
            wait_step(wbars, e);
            gemv_load(f, slot_addr(wslots, e), lane);
            asm volatile("" :: "r"(f[7][3]), "r"(f[6][3]) : "memory");
            refill_if(p, e, wslots, wbars, w);
            if (layer > 0) {
                int it = 0;
                while (!__all_sync(FULL, (((v[0][0] ^ ptag) | (v[1][0] ^ ptag) | (v[2][0] ^ ptag) | (v[3][0] ^ ptag)) & 3u) == 0u) && ++it < SPIN_LIMIT) {
#pragma unroll
                    for (int j = 0; j < 4; j++)
                        if ((v[j][0] ^ ptag) & 3u) ld_rlx16(v[j], src + j * 1024);
                }
                xp = add_residual(xp, v, half);
                TSTAMP(layer * 8);
            }
            refill_if(p, p.steps[c + 1], wslots, wbars, w);
            float y0, y1, st[4];
            gemv_mma<true>(f, xp, y0, y1, st, lane);
            float* dst = pin(&p.xc->q[cta][2 * lane]);
            sts2(smem + OFF_RED + w * 256 + (8 * (lane & 3) + (lane >> 2)) * 8, y0, y1);
            if (lane == 0) sts2(smem + OFF_ST + w * 8, st[0], st[1]);
            __syncthreads();
            if (w == 0) {
                float u[8][4], z[16];
#pragma unroll
                for (int i = 0; i < 4; i++) lds4(z + 4 * i, smem + OFF_ST + 16 * i);
#pragma unroll
                for (int i = 0; i < 8; i++) lds4(u[i], smem + OFF_RED + i * 256 + (lane & 15) * 16);
                const float sq = ((z[0] + z[2]) + (z[4] + z[6])) + ((z[8] + z[10]) + (z[12] + z[14]));
                const float su = ((z[1] + z[3]) + (z[5] + z[7])) + ((z[9] + z[11]) + (z[13] + z[15]));
                const float mean = su * (1.f / 512.f);
                const float rstd = rsq(fmaxf(fmaf(-mean, mean, sq * (1.f / 512.f)), 0.f) + 1e-5f);
                float r[4];
#pragma unroll
                for (int k = 0; k < 4; k++) r[k] = ((u[0][k] + u[1][k]) + (u[2][k] + u[3][k])) + ((u[4][k] + u[5][k]) + (u[6][k] + u[7][k]));
                if (lane < 16) st_rlx8(dst, tagged(fmaf(-mean, r[1], r[0]) * rstd, tag), __float_as_uint(fmaf(-mean, r[3], r[2]) * rstd));
            }
            TSTAMP(2 + layer * 8);
            refill_if(p, p.steps[c + 2], wslots, wbars, w);
            refill_if(p, p.steps[c + 3], wslots, wbars, w);
            c += 4;
            __syncthreads();
        }
        const uint32_t offk = (((lane >> 3) & 1) * 8 + (lane & 7)) * 128 + ((((lane >> 4) & 1) ^ (lane & 7)) << 4);
        const uint32_t offv = (((lane >> 4) & 1) * 8 + (lane & 7)) * 128 + ((((lane >> 3) & 1) ^ (lane & 7)) << 4);
        a.mv = pin((((lane >> 2) ^ (lane >> 1)) & 1) - 1u);
        uint32_t f[32];
        if (layer & 1) {
            const uint32_t e = p.steps[c];
            wait_step(wbars, e);
            load_k(f, slot_addr(wslots, e) + offk);
            asm volatile("" :: "r"(f[31]), "r"(f[27]) : "memory");
            refill_if(p, e, wslots, wbars, w);
        } else {
#pragma unroll
            for (int i = 0; i < 32; i++) f[i] = 0u;
        }
        {
            const float* qsrc = pin(&p.xc->q[h * 16 + 2 * w][2 * lane]);
            const uint32_t qd = pin(smem + OFF_RED + ((lane >> 4) * 32 + 4 * ((w >> 1) + 4 * (w & 1)) + (lane & 3)) * 16 + (lane & 12));
            uint32_t v0, v1;
            int it = 0;
            do { ld_rlx8(v0, v1, qsrc); } while (!__all_sync(FULL, ((v0 ^ tag) & 3u) == 0u) && ++it < SPIN_LIMIT);
            sts(qd, __uint_as_float(pack_bf16(__uint_as_float(v0), __uint_as_float(v1))));
            __syncthreads();
            lds4(reinterpret_cast<float*>(a.qf), smem + OFF_RED + lane * 16);
            lds4(reinterpret_cast<float*>(a.qf + 4), smem + OFF_RED + 512 + lane * 16);
        }
        TSTAMP(3 + layer * 8);
        if (layer & 1) {
            const uint32_t ek1 = p.steps[c + 1], ev0 = p.steps[c + 2], ev = p.steps[c + 3];
            uint32_t b[8];
            float s[8];
            qk(a, f, s);
            wait_step(wbars, ek1);
            load_k(f, slot_addr(wslots, ek1) + offk);
            qk(a, f, s + 4);
            refill(p, ek1, wslots, wbars, w);
#pragma unroll
            for (int i = 0; i < 8; i++) s[i] += __shfl_xor_sync(FULL, s[i], 6);
            float t0 = fmaxf(fmaxf(s[0], s[2]), fmaxf(s[4], s[6])), t1 = fmaxf(fmaxf(s[1], s[3]), fmaxf(s[5], s[7]));
#pragma unroll
            for (int d = 4; d <= 16; d <<= 1) {
                t0 = fmaxf(t0, __shfl_xor_sync(FULL, t0, d));
                t1 = fmaxf(t1, __shfl_xor_sync(FULL, t1, d));
            }
            a.n0 = -SCALE_LOG2E * t0; a.n1 = -SCALE_LOG2E * t1;
            a.l0 = a.l1 = 0.f;
#pragma unroll
            for (int i = 0; i < 8; i++) s[i] = fmaf(s[i], SCALE_LOG2E, (i & 1) ? a.n1 : a.n0);
            wait_step(wbars, ev0);
            load_v(f, slot_addr(wslots, ev0) + offv);
            probs(a, s, b);
            probs(a, s + 4, b + 4);
#pragma unroll
            for (int i = 0; i < 16; i++) a.o[i] = 0.f;
            pv(a, f, b);
            refill(p, ev0, wslots, wbars, w);
            wait_step(wbars, ev);
            load_v(f, slot_addr(wslots, ev) + offv);
            pv(a, f, b + 4);
        } else {
#pragma unroll
            for (int i = 0; i < 16; i++) a.o[i] = 0.f;
            a.n0 = a.n1 = INFINITY;
            a.l0 = a.l1 = 0.f;
#pragma unroll 1
            for (;;) {
                const uint32_t rfmask = p.steps[c] >> 20;
                if (rfmask) {
#pragma unroll
                    for (int r = 0; r < NRF; r++) if ((rfmask >> r) & 1u) {
                        float s[4];
                        uint32_t b[4];
                        if (layer == 0) {
                            const uint32_t e = p.steps[c++];
                            wait_step(wbars, e);
                            load_k(rk[r], slot_addr(wslots, e) + offk);
                            asm volatile("" :: "r"(rk[r][31]), "r"(rk[r][27]) : "memory");
                            refill(p, e, wslots, wbars, w);
                        }
                        qk(a, rk[r], s);
                        softmax_step(a, s, b);
                        if (layer == 0) {
                            const uint32_t e = p.steps[c++];
                            wait_step(wbars, e);
                            load_v(rv[r], slot_addr(wslots, e) + offv);
                            asm volatile("" :: "r"(rv[r][31]), "r"(rv[r][23]) : "memory");
                            refill(p, e, wslots, wbars, w);
                        }
                        pv(a, rv[r], b);
                    }
                }
                float s[4];
                uint32_t b[4];
                const uint32_t ek = p.steps[c++];
                const uint32_t ev = p.steps[c++];
                wait_step(wbars, ek);
                load_k(f, slot_addr(wslots, ek) + offk);
                qk(a, f, s);
                refill(p, ek, wslots, wbars, w);
                softmax_step(a, s, b);
                wait_step(wbars, ev);
                load_v(f, slot_addr(wslots, ev) + offv);
                pv(a, f, b);
                refill(p, ev, wslots, wbars, w);
                if (ev & STEP_LAST) break;
            }
        }
        c = p.last[layer] + 1;
        const uint32_t ev = p.steps[c++];
        lane = lane_id();
        const int g = lane >> 2, t = lane & 3, half = lane >> 4, c16 = lane & 15;
        TSTAMP(4 + layer * 8);
        uint32_t v[8][4], mj, lj;
        const float* src = pin(&p.xc->part[h * 16 + half][w][4 * c16]);
        const float* ssrc = pin(&p.xc->part[h * 16 + c16][w][64]);
        {
            a.l0 += __shfl_xor_sync(FULL, a.l0, 4);
            a.l1 += __shfl_xor_sync(FULL, a.l1, 4);
            a.l0 += __shfl_xor_sync(FULL, a.l0, 8);
            a.l1 += __shfl_xor_sync(FULL, a.l1, 8);
            const uint32_t o0 = slot_addr(wslots, ev) + ((4 * (t & 1) + (t >> 1)) * 96 + 8 * t + g) * 4;
#pragma unroll
            for (int i = 0; i < 4; i++) {
                sts(o0 + i * 64, a.o[4 * i]);
                sts(o0 + i * 64 + 192 * 4, a.o[4 * i + 1]);
                sts(o0 + i * 64 + 32, a.o[4 * i + 2]);
                sts(o0 + i * 64 + 192 * 4 + 32, a.o[4 * i + 3]);
            }
            a.l0 += __shfl_xor_sync(FULL, a.l0, 16);
            a.l1 += __shfl_xor_sync(FULL, a.l1, 16);
            if (lane < 2) {
                const uint32_t ml = smem + OFF_ML + lane * 128 + w * 4;
                sts(ml, -a.n0); sts(ml + 64, -a.n1); sts(ml + 32, a.l0); sts(ml + 96, a.l1);
            }
            float* dst = pin(&p.xc->part[cta][w][4 * lane]);
            const uint32_t mlr = pin(smem + OFF_ML + (w >> 1) * 64 + half * 16);
            const uint32_t ro = pin(slot_addr(smem, ev) + half * (4 * NSLOT * TILE) + (w * 96 + 8 * ((w >> 2) + 2 * (w & 1)) + 4 * c16) * 4);
            __syncthreads();
            float m[8], l[4], u[4][4];
            lds4(m, mlr);
            lds4(m + 4, mlr ^ 16u);
#pragma unroll
            for (int i = 0; i < 4; i++) lds4(u[i], ro + i * (NSLOT * TILE));
            lds4(l, mlr + 32);
            const float M = fmaxf(fmaxf(fmaxf(m[0], m[1]), fmaxf(m[2], m[3])), fmaxf(fmaxf(m[4], m[5]), fmaxf(m[6], m[7])));
            float z[4], r[4];
#pragma unroll
            for (int i = 0; i < 4; i++) z[i] = ex2(m[i] - M);
#pragma unroll
            for (int k = 0; k < 4; k++) r[k] = fmaf(z[0], u[0][k], z[1] * u[1][k]) + fmaf(z[2], u[2][k], z[3] * u[3][k]);
            float L = fmaf(z[0], l[0], z[1] * l[1]) + fmaf(z[2], l[2], z[3] * l[3]);
#pragma unroll
            for (int k = 0; k < 4; k++) r[k] += __shfl_xor_sync(FULL, r[k], 16);
            L += __shfl_xor_sync(FULL, L, 16);
            if (lane <= 16) st_rlx16(dst, tagged(selp(M, r[0], half), tag), __float_as_uint(selp(L, r[1], half)), __float_as_uint(r[2]), __float_as_uint(r[3]));
            TSTAMP(5 + layer * 8);
            ld_rlx8(mj, lj, ssrc);
#pragma unroll
            for (int j = 0; j < 8; j++) ld_rlx16(v[j], src + j * (2 * NW * 96));
            asm volatile("fence.proxy.async.shared::cta;" ::: "memory");
            __syncthreads();
            refill_if(p, ev, wslots, wbars, w);
            refill_if(p, p.steps[c], wslots, wbars, w);
        }
        {
            const uint32_t e = p.steps[c + 1];
            int it = 0;
            for (;;) {
                uint32_t bad = mj ^ tag;
#pragma unroll
                for (int j = 0; j < 8; j++) bad |= v[j][0] ^ tag;
                if (__all_sync(FULL, (bad & 3u) == 0u) || ++it >= SPIN_LIMIT) break;
                if (!(layer & 1) && __popc(__ballot_sync(FULL, (mj ^ tag) & 3u)) > 4) __nanosleep(p.nap);
                if ((mj ^ tag) & 3u) ld_rlx8(mj, lj, ssrc);
#pragma unroll
                for (int j = 0; j < 8; j++)
                    if ((v[j][0] ^ tag) & 3u) ld_rlx16(v[j], src + j * (2 * NW * 96));
            }
            TSTAMP(6 + layer * 8);
            const int key = (int)mj ^ (((int)mj >> 31) & 0x7fffffff);
            const int kmax = __reduce_max_sync(FULL, key);
            const float M = __int_as_float(kmax ^ ((kmax >> 31) & 0x7fffffff));
            const float fo = ex2(__uint_as_float(mj) - M);
            float fj[8], r[4];
#pragma unroll
            for (int j = 0; j < 8; j++) fj[j] = __shfl_sync(FULL, fo, 2 * j + half);
#pragma unroll
            for (int k = 0; k < 4; k++) {
                float r0 = fj[0] * __uint_as_float(v[0][k]), r1 = fj[1] * __uint_as_float(v[1][k]);
#pragma unroll
                for (int j = 2; j < 8; j += 2) { r0 = fmaf(fj[j], __uint_as_float(v[j][k]), r0); r1 = fmaf(fj[j + 1], __uint_as_float(v[j + 1][k]), r1); }
                r[k] = r0 + r1;
            }
            const float y0 = selp(r[2], r[0], half) + __shfl_xor_sync(FULL, selp(r[0], r[2], half), 16);
            const float y1 = selp(r[3], r[1], half) + __shfl_xor_sync(FULL, selp(r[1], r[3], half), 16);
            refill_if(p, p.steps[c + 2], wslots, wbars, w);
            wait_step(wbars, e);
            uint32_t fw[8][4];
            gemv_load(fw, slot_addr(wslots, e), lane);
            float L = fo * __uint_as_float(lj);
#pragma unroll
            for (int d = 1; d < 16; d <<= 1) L += __shfl_xor_sync(FULL, L, d);
            float y, unused;
            gemv_mma<false>(fw, pack_bf16(y0, y1), y, unused, nullptr, lane);
            float* dst = pin(&p.xc->x[layer & 1][cta][4 * lane]);
            sts(smem + OFF_RED + w * 128 + (8 * t + g) * 4, y * rcp(L));
            __syncthreads();
            if (w == 0) {
                float u[8][4];
#pragma unroll
                for (int i = 0; i < 8; i++) lds4(u[i], smem + OFF_RED + i * 128 + (lane & 7) * 16);
#pragma unroll
                for (int k = 0; k < 4; k++) r[k] = ((u[0][k] + u[1][k]) + (u[2][k] + u[3][k])) + ((u[4][k] + u[5][k]) + (u[6][k] + u[7][k]));
                if (lane < 8) st_rlx16(dst, tagged(r[0], tag), __float_as_uint(r[1]), __float_as_uint(r[2]), __float_as_uint(r[3]));
            }
            TSTAMP(7 + layer * 8);
            refill_if(p, e, wslots, wbars, w);
            refill_if(p, p.steps[c + 3], wslots, wbars, w);
            __syncthreads();
        }
    }
    if (cta == 0) {
        const float* src = &p.xc->x[1][16 * (lane >> 4) + 2 * w][4 * (lane & 15)];
        uint32_t v[4][4];
        int it = 0;
        do {
#pragma unroll
            for (int j = 0; j < 4; j++) ld_rlx16(v[j], src + j * 1024);
        } while (!__all_sync(FULL, ((v[0][0] | v[1][0] | v[2][0] | v[3][0]) & 3u) == 0u) && ++it < SPIN_LIMIT);
        reinterpret_cast<uint32_t*>(p.out)[32 * w + 2 * (lane & 15) + (lane >> 4)] = add_residual(xp, v, lane >> 4);
        TSTAMP(32);
    }
}

typedef CUresult (*EncodeFn)(CUtensorMap*, CUtensorMapDataType, cuuint32_t, void*, const cuuint64_t*, const cuuint64_t*,
                             const cuuint32_t*, const cuuint32_t*, CUtensorMapInterleave, CUtensorMapSwizzle,
                             CUtensorMapL2promotion, CUtensorMapFloatOOBfill);

void encode5d(EncodeFn enc, CUtensorMap* m, const void* ptr, uint32_t cols, uint32_t rows, uint32_t nchunk,
              uint64_t srow, uint64_t schunk, uint64_t ss, uint64_t sh, CUtensorMapSwizzle sw, CUtensorMapL2promotion promo) {
    cuuint64_t dims[5] = {cols, rows, nchunk, 16, 8};
    cuuint64_t strides[4] = {srow, schunk, ss, sh};
    cuuint32_t box[5] = {cols, rows, 1, 1, 1};
    cuuint32_t es[5] = {1, 1, 1, 1, 1};
    CUresult r = enc(m, CU_TENSOR_MAP_DATA_TYPE_BFLOAT16, 5, const_cast<void*>(ptr), dims, strides, box, es,
        CU_TENSOR_MAP_INTERLEAVE_NONE, sw, promo, CU_TENSOR_MAP_FLOAT_OOB_FILL_NONE);
    (void)r;
}

struct Sched {
    int nkeep = 6;
    int nl2 = 15;
    int konly = 1;
    int promoB = 0;
    int promoW = 0;
    int rf1 = 333;
    int rf3 = 468;
    int d0 = 4;
    int d1 = 2;
    int d3 = 5;
    int ch1 = 111111111, ch2 = 111101100, ch3 = 222324234;
    int nap = 0;
};

void build_schedule(Params& p, const Sched& sc) {
    struct Item { int map, tile, promote, park; };
    Item items[96];
    int n = 0;
    auto add = [&](int map, int tile, int promote, int park = 0) { items[n] = Item{map, tile, promote, park}; return n++; };
    auto dig = [](int v, int i) { for (int k = 8; k > i; k--) v /= 10; return v % 10; };
    const int rf0 = 3, lo = rf0 + NRF;
    bool inl2[32] = {false};
    if (sc.konly) {
        int left = sc.nl2;
        for (int u = 30; u >= 2 * lo && left > 0; u -= 2, left--) inl2[u] = true;
        for (int u = 31; u >= 2 * lo && left > 0; u -= 2, left--) inl2[u] = true;
    } else {
        for (int u = 32 - sc.nl2; u < 32; u++) inl2[u] = true;
    }
    int c1[32], n1 = 0, c3[32], n3 = 0, rfat1[32] = {0};
    const bool late = sc.nkeep == 6;
    const int wq1 = add(M_WQA, 0, 0);
    int v2 = -1;
    for (int sp = 0; sp < 16 - NRF; sp++) {
        const int at = n1;
        for (int r = 0; r < NRF; r++)
            if (dig(sc.rf1, 6 + r) == sp) { rfat1[at] |= 1 << r; c1[n1++] = add(0, rf0 + r, 0); c1[n1++] = add(1, rf0 + r, 0); }
        int pr = sp < rf0 ? sp : sp + NRF;
        if (late) {
            if (sp == 2) v2 = add(1, 2, 0, 1);
            pr = sp < 2 ? sp : (sp == 15 - NRF ? 2 : sp + NRF + 1);
        }
        c1[n1++] = add(0, pr, inl2[2 * pr]);
        c1[n1++] = late && pr == 2 ? v2 : add(1, pr, inl2[2 * pr + 1]);
    }
    auto keep1 = [&](int it) { return 2 * items[it].tile + items[it].map < sc.nkeep; };
    const int tail1 = n;
    add(M_WOA, 0, sc.promoW & 1);
    add(M_WQB, 0, sc.promoB & 1);
    for (int u = 0; u < 4; u++) add(M_KB + (u >> 1), u & 1, (sc.promoB >> (1 + u)) & 1);
    add(M_WOB, 0, (sc.promoB >> 5) & 1);
    add(M_WQA, 0, 0);
    for (int u = 0; u < 2 * rf0; u++) {
        int it = -1;
        for (int i = 0; i < n1; i++) if (keep1(c1[i]) && 2 * items[c1[i]].tile + items[c1[i]].map == u) it = c1[i];
        c3[n3++] = it >= 0 ? it : add(u & 1, u >> 1, 0);
    }
    int l2first = 16;
    while (l2first > lo && inl2[2 * l2first - 1]) l2first--;
    const int nd = l2first - lo, nh = 16 - l2first;
    int di = 0, hi_i = 0;
    while (di < nd || hi_i < nh) {
        const bool takeD = hi_i >= nh || (di < nd && di * nh <= hi_i * nd);
        const int pr = takeD ? lo + di++ : 15 - hi_i++;
        c3[n3++] = add(0, pr, 0); c3[n3++] = add(1, pr, 0);
    }
    const int tail3 = n;
    add(M_WOA, 0, 0); add(M_WQB, 0, 0);
    for (int u = 0; u < 4; u++) add(M_KB + (u >> 1), u & 1, 0);
    add(M_WOB, 0, 0);
    int slot_of[96], pending[96] = {0}, fre[16], nfree = 0, par[NSLOT] = {0}, ic = NFIRST, c = 0, nq = NFIRST, reserve = 0;
    for (int i = 0; i < NFIRST; i++) { slot_of[i] = i; pending[i] = 1; }
    for (int i = NSLOT - 1; i >= NFIRST; i--) fre[nfree++] = i;
    for (int i = 0; i < NSTEP; i++) p.steps[i] = 0;
    auto load = [&](int depth) -> uint32_t {
        if (!(ic < n && nfree > reserve && nq < depth)) return 0;
        const Item& it = items[ic];
        const int dst = slot_of[ic] = fre[--nfree];
        if (!it.park) { pending[ic] = 1; nq++; }
        ic++;
        return 16 | (it.promote << 5) | (it.map << 6) | (it.tile << 9) | (dst << 16);
    };
    auto extra = [&](int depth) { p.steps[c++] = load(depth); };
    auto consume = [&](int it, bool keep) -> uint32_t {
        const int slot = slot_of[it];
        if (pending[it]) { pending[it] = 0; nq--; }
        const uint32_t e = slot | (par[slot] << 3);
        if (!keep) { par[slot] ^= 1; fre[nfree++] = slot; }
        return e;
    };
    auto step = [&](int it, bool keep, int depth) { const uint32_t e = consume(it, keep); p.steps[c++] = e | load(depth); };
    auto atleast1 = [](int d) { return d < 1 ? 1 : d; };
    int layer = 0;
    auto chain = [&](int t0, bool keep0, int t1, bool keep1_, int wo, int wq, int d) {
        reserve = keep1_ ? 1 : 0;
        step(t0, keep0, atleast1(dig(d, 0)));
        reserve = 0;
        p.steps[c++] = consume(t1, keep1_) | STEP_LAST;
        p.last[layer++] = c - 1;
        const int scratch = fre[nfree - 1];
        extra(atleast1(dig(d, 1))); p.steps[c - 1] |= scratch;
        extra(dig(d, 1));
        const int at = c++;
        extra(dig(d, 2));
        p.steps[at] = consume(wo, false);
        p.steps[at] |= load(atleast1(dig(d, 3)));
        extra(dig(d, 3));
        if (wq < 0) return;
        p.first[layer] = c;
        step(wq, false, dig(d, 4));
        extra(dig(d, 5));
        extra(atleast1(dig(d, 6))); extra(dig(d, 6));
    };
    p.first[0] = 0;
    p.nap = sc.nap;
    step(wq1, false, 0); extra(0); extra(sc.d0); extra(sc.d0);
    for (int u = 0; u < 30; u++) {
        if (late && u == 29) reserve = 1;
        step(c1[u], keep1(c1[u]), u < 2 ? sc.d0 : sc.d1);
        p.steps[c - 1] |= rfat1[u] * STEP_RF;
    }
    chain(c1[30], keep1(c1[30]), c1[31], keep1(c1[31]), tail1, tail1 + 1, sc.ch1);
    step(tail1 + 2, false, atleast1(dig(sc.ch1, 7))); step(tail1 + 3, false, atleast1(dig(sc.ch1, 8)));
    chain(tail1 + 4, false, tail1 + 5, false, tail1 + 6, tail1 + 7, sc.ch2);
    for (int u = 0; u < n3 - 2; u++) {
        const int cap = n3 - (u + 1) + dig(sc.ch3, 0) - 1;
        step(c3[u], false, sc.d3 < cap ? sc.d3 : cap);
        for (int r = 0; r < NRF; r++) if (u == 2 * dig(sc.rf3, 6 + r)) p.steps[c - 1] |= STEP_RF << r;
    }
    chain(c3[n3 - 2], false, c3[n3 - 1], false, tail3, tail3 + 1, sc.ch3);
    step(tail3 + 2, false, atleast1(dig(sc.ch3, 7))); step(tail3 + 3, false, atleast1(dig(sc.ch3, 8)));
    chain(tail3 + 4, false, tail3 + 5, false, tail3 + 6, -1, 777777777);
}

Sched g_sched;

}

extern "C" void kernel_launch(void* const* d_in, const int* in_sizes, int n_in, void* d_out, int out_size) {
    (void)in_sizes; (void)n_in; (void)out_size;
    void* fn = nullptr;
    cudaDriverEntryPointQueryResult qr;
    cudaGetDriverEntryPoint("cuTensorMapEncodeTiled", &fn, cudaEnableDefault, &qr);
    EncodeFn enc = (EncodeFn)fn;
    Params p;
    const CUtensorMapL2promotion pk = CU_TENSOR_MAP_L2_PROMOTION_L2_256B, pw = CU_TENSOR_MAP_L2_PROMOTION_NONE;
    const size_t win = (size_t)28672 * 256;
    encode5d(enc, &p.maps[M_KA], d_in[1], 64, 32, 128, 128, 4096, 512 << 10, 8 << 20, CU_TENSOR_MAP_SWIZZLE_128B, pk);
    encode5d(enc, &p.maps[M_VA], d_in[2], 64, 32, 128, 128, 4096, 512 << 10, 8 << 20, CU_TENSOR_MAP_SWIZZLE_128B, pk);
    encode5d(enc, &p.maps[M_KB], (const char*)d_in[6] + win, 64, 32, 16, 128, 4096, 64 << 10, 8 << 20, CU_TENSOR_MAP_SWIZZLE_128B, pk);
    encode5d(enc, &p.maps[M_VB], (const char*)d_in[7] + win, 64, 32, 16, 128, 4096, 64 << 10, 8 << 20, CU_TENSOR_MAP_SWIZZLE_128B, pk);
    encode5d(enc, &p.maps[M_WQA], d_in[3], 32, 64, 8, 8192, 64 * 8192, 64, 1024, CU_TENSOR_MAP_SWIZZLE_64B, pw);
    encode5d(enc, &p.maps[M_WQB], d_in[8], 32, 64, 8, 8192, 64 * 8192, 64, 1024, CU_TENSOR_MAP_SWIZZLE_64B, pw);
    encode5d(enc, &p.maps[M_WOA], d_in[4], 32, 64, 8, 1024, 64 << 10, 64, 512 << 10, CU_TENSOR_MAP_SWIZZLE_64B, pw);
    encode5d(enc, &p.maps[M_WOB], d_in[9], 32, 64, 8, 1024, 64 << 10, 64, 512 << 10, CU_TENSOR_MAP_SWIZZLE_64B, pw);
    void* xc = nullptr;
    cudaGetSymbolAddress(&xc, g_xchg);
    p.xc = (Xchg*)xc;
    p.x = (const __nv_bfloat16*)d_in[0];
    p.out = (__nv_bfloat16*)d_out;
    build_schedule(p, g_sched);
    cudaFuncSetAttribute(decode_kernel, cudaFuncAttributeMaxDynamicSharedMemorySize, SMEM_BYTES);
    decode_kernel<<<NCTA, NW * 32, SMEM_BYTES, cudaStreamPerThread>>>(p);
}
```

```cpp
#include <cuda_runtime.h>
#include <cuda_bf16.h>
#include <cuda.h>
#include <stdint.h>

namespace {

constexpr int NCTA  = 128;
constexpr int NW    = 8;
constexpr int NSLOT = 7;
constexpr int TILE  = 4096;
constexpr int NFIRST = 3;
constexpr int NRF = 4;

constexpr int OFF_BAR = NW * NSLOT * TILE;
constexpr int OFF_RED = OFF_BAR + 512;
constexpr int OFF_ST  = OFF_RED + 2048;
constexpr int OFF_ML  = OFF_ST + 64;
constexpr int OFF_META = OFF_ML + 256;
constexpr int SMEM_BYTES = OFF_META + 128;

constexpr uint64_t POL_EVICT_FIRST = 0x12F0000000000000ull;
constexpr int SPIN_LIMIT = 1 << 20;
constexpr unsigned FULL = 0xffffffffu;

enum { M_KA = 0, M_VA = 1, M_KB = 2, M_VB = 3, M_WQA = 4, M_WQB = 5, M_WOA = 6, M_WOB = 7 };

constexpr uint32_t STEP_LAST = 1u << 13, STEP_RF = 1u << 20;
constexpr int NSTEP = 120;
struct Xchg {
    float q[NCTA][32];
    float part[NCTA][NW][96];
    float x[2][NCTA][32];
};
struct __align__(64) Params {
    CUtensorMap maps[8];
    const __nv_bfloat16* x;
    __nv_bfloat16* out;
    Xchg* xc;
    int first[4], last[4];
    uint32_t steps[NSTEP];
};
__device__ __align__(128) Xchg g_xchg;
#define TSTAMP(i)

__device__ __forceinline__ int lane_id() { int l; asm volatile("mov.u32 %0, %%laneid;" : "=r"(l)); return l; }
__device__ __forceinline__ bool mbar_try(uint32_t bar, uint32_t parity) {
    uint32_t ok;
    asm volatile("{\n.reg .pred p;\nmbarrier.try_wait.parity.shared::cta.b64 p, [%1], %2;\nselp.u32 %0, 1, 0, p;\n}"
                 : "=r"(ok) : "r"(bar), "r"(parity) : "memory");
    return __all_sync(0xffffffffu, ok);
}
__device__ __forceinline__ void mbar_wait(uint32_t bar, uint32_t parity) {
    if (!mbar_try(bar, parity)) {
        int n = 0;
        while (!mbar_try(bar, parity) && ++n < (1 << 17)) {}
    }
}
__device__ __forceinline__ void ldsm4(uint32_t* r, uint32_t a) {
    asm volatile("ldmatrix.sync.aligned.m8n8.x4.shared.b16 {%0,%1,%2,%3}, [%4];"
                 : "=r"(r[0]), "=r"(r[1]), "=r"(r[2]), "=r"(r[3]) : "r"(a) : "memory");
}
__device__ __forceinline__ void ldsm4t(uint32_t* r, uint32_t a) {
    asm volatile("ldmatrix.sync.aligned.m8n8.x4.trans.shared.b16 {%0,%1,%2,%3}, [%4];"
                 : "=r"(r[0]), "=r"(r[1]), "=r"(r[2]), "=r"(r[3]) : "r"(a) : "memory");
}
__device__ __forceinline__ void mma16816(float* c, uint32_t a0, uint32_t a1, uint32_t a2, uint32_t a3, uint32_t b0, uint32_t b1) {
    asm volatile("mma.sync.aligned.m16n8k16.row.col.f32.bf16.bf16.f32 {%0,%1,%2,%3}, {%4,%5,%6,%7}, {%8,%9}, {%0,%1,%2,%3};"
                 : "+f"(c[0]), "+f"(c[1]), "+f"(c[2]), "+f"(c[3])
                 : "r"(a0), "r"(a1), "r"(a2), "r"(a3), "r"(b0), "r"(b1));
}
__device__ __forceinline__ void mma16816(float* c, const uint32_t* a, uint32_t b0, uint32_t b1) { mma16816(c, a[0], a[1], a[2], a[3], b0, b1); }
__device__ __forceinline__ uint32_t movm(uint32_t a) {
    uint32_t d;
    asm volatile("movmatrix.sync.aligned.m8n8.trans.b16 %0, %1;" : "=r"(d) : "r"(a));
    return d;
}
__device__ __forceinline__ uint32_t pack_bf16(float lo, float hi) {
    uint32_t d;
    asm("cvt.rn.bf16x2.f32 %0, %1, %2;" : "=r"(d) : "f"(hi), "f"(lo));
    return d;
}
__device__ __forceinline__ float bf_lo(uint32_t v) { return __uint_as_float(v << 16); }
__device__ __forceinline__ float bf_hi(uint32_t v) { return __uint_as_float(v & 0xffff0000u); }
__device__ __forceinline__ float ex2(float v) { float d; asm("ex2.approx.ftz.f32 %0, %1;" : "=f"(d) : "f"(v)); return d; }
__device__ __forceinline__ float rcp(float v) { float d; asm("rcp.approx.ftz.f32 %0, %1;" : "=f"(d) : "f"(v)); return d; }
__device__ __forceinline__ float rsq(float v) { float d; asm("rsqrt.approx.ftz.f32 %0, %1;" : "=f"(d) : "f"(v)); return d; }
__device__ __forceinline__ uint32_t tagged(float v, uint32_t tag) { return (__float_as_uint(v) & ~3u) | tag; }

__device__ __forceinline__ void st_rlx8(void* p, uint32_t a, uint32_t b) {
    asm volatile("{\n.reg .b64 l;\nmov.b64 l, {%1,%2};\nst.relaxed.gpu.global.b64 [%0], l;\n}" :: "l"(p), "r"(a), "r"(b) : "memory");
}
__device__ __forceinline__ void ld_rlx8(uint32_t& a, uint32_t& b, const void* p) {
    asm volatile("{\n.reg .b64 l;\nld.relaxed.gpu.global.b64 l, [%2];\nmov.b64 {%0,%1}, l;\n}" : "=r"(a), "=r"(b) : "l"(p) : "memory");
}
__device__ __forceinline__ void st_rlx16(void* p, uint32_t a, uint32_t b, uint32_t c, uint32_t d) {
    asm volatile("{\n.reg .b64 l, h;\n.reg .b128 v;\nmov.b64 l, {%1,%2};\nmov.b64 h, {%3,%4};\nmov.b128 v, {l,h};\n"
                 "st.relaxed.gpu.global.b128 [%0], v;\n}" :: "l"(p), "r"(a), "r"(b), "r"(c), "r"(d) : "memory");
}
__device__ __forceinline__ void ld_rlx16(uint32_t* r, const void* p) {
    asm volatile("{\n.reg .b64 l, h;\n.reg .b128 v;\nld.relaxed.gpu.global.b128 v, [%4];\nmov.b128 {l,h}, v;\n"
                 "mov.b64 {%0,%1}, l;\nmov.b64 {%2,%3}, h;\n}" : "=r"(r[0]), "=r"(r[1]), "=r"(r[2]), "=r"(r[3]) : "l"(p) : "memory");
}
__device__ __forceinline__ void sts(uint32_t a, float v) { asm volatile("st.shared.f32 [%0], %1;" :: "r"(a), "f"(v) : "memory"); }
__device__ __forceinline__ void sts2(uint32_t a, float x, float y) { asm volatile("st.shared.v2.f32 [%0], {%1,%2};" :: "r"(a), "f"(x), "f"(y) : "memory"); }
__device__ __forceinline__ void lds4(float* v, uint32_t a) { asm volatile("ld.shared.v4.f32 {%0,%1,%2,%3}, [%4];" : "=f"(v[0]), "=f"(v[1]), "=f"(v[2]), "=f"(v[3]) : "r"(a) : "memory"); }

constexpr float SCALE_LOG2E = 0.08838834764831845f * 1.4426950408889634f;
constexpr float MAX_SLACK = 8.f;

__device__ __forceinline__ uint32_t slot_addr(uint32_t wslots, uint32_t e) { return wslots + (e & 7u) * TILE; }
__device__ __forceinline__ uint32_t slot_bar(uint32_t wbars, uint32_t e) { return wbars + (e & 7u) * 8; }
__device__ __forceinline__ void wait_step(uint32_t wbars, uint32_t e) { mbar_wait(slot_bar(wbars, e), (e >> 3) & 1u); }
__device__ __forceinline__ void refill(const Params& p, uint32_t e, uint32_t wslots, uint32_t wbars, int w) {
    const unsigned char* m = reinterpret_cast<const unsigned char*>(&p.maps[0]) + ((e << 1) & 0x380u);
    const int c2 = w + ((e >> 6) & 0x78u), c3 = blockIdx.x & 15, c4 = blockIdx.x >> 4;
    asm volatile("{\n.reg .pred p, q;\n"
                 "elect.sync _|p, 0xffffffff;\n"
                 "setp.ne.and.u32 q, %9, 0, p;\n"
                 "setp.ne.and.u32 p, %8, 0, p;\n"
                 "@p mbarrier.arrive.expect_tx.shared::cta.b64 _, [%6], 4096;\n"
                 "@p cp.async.bulk.tensor.5d.shared::cluster.global.mbarrier::complete_tx::bytes.L2::cache_hint [%0], [%1, {%2,%2,%3,%4,%5}], [%6], %7;\n"
                 "@q cp.async.bulk.prefetch.tensor.5d.L2.global.tile [%1, {%2,%2,%3,%4,%5}];\n"
                 "}"
                 :: "r"(slot_addr(wslots, e >> 16)), "l"(m), "r"(0), "r"(c2), "r"(c3), "r"(c4), "r"(slot_bar(wbars, e >> 16)), "l"(POL_EVICT_FIRST),
                    "r"(e & 16u), "r"(e & 32u) : "memory");
}

__device__ __forceinline__ void refill_if(const Params& p, uint32_t e, uint32_t wslots, uint32_t wbars, int w) {
    if (e & 48u) refill(p, e, wslots, wbars, w);
}
template <class T> __device__ __forceinline__ T* pin(T* q) { asm volatile("" : "+l"(q)); return q; }
__device__ __forceinline__ uint32_t pin(uint32_t v) { asm volatile("" : "+r"(v)); return v; }
__device__ __forceinline__ float selp(float a, float b, bool c) {
    float d;
    asm("{\n.reg .pred p;\nsetp.ne.u32 p, %3, 0;\nselp.f32 %0, %1, %2, p;\n}" : "=f"(d) : "f"(a), "f"(b), "r"((uint32_t)c));
    return d;
}

constexpr uint32_t SWAP = 0x90;
struct Attn {
    uint32_t qf[8];
    float o[16];
    float n0, n1;
    float l0, l1;
    uint32_t mv;
};
__device__ __forceinline__ void load_k(uint32_t* f, uint32_t base) {
#pragma unroll
    for (int j = 0; j < 4; j++) {
        ldsm4(f + 8 * j, base ^ (j << 5));
        ldsm4(f + 8 * j + 4, (base ^ (j << 5) ^ SWAP) + 2048);
    }
}
__device__ __forceinline__ void load_v(uint32_t* f, uint32_t base) {
#pragma unroll
    for (int j = 0; j < 4; j++) ldsm4t(f + 8 * j, base ^ (j << 5));
#pragma unroll
    for (int j = 0; j < 4; j++) ldsm4t(f + 8 * j + 4, (base ^ (j << 5) ^ SWAP) + 2048);
}
__device__ __forceinline__ void qk(const Attn& a, const uint32_t* f, float* s) {
    float c[8];
#pragma unroll
    for (int i = 0; i < 8; i++) c[i] = 0.f;
#pragma unroll
    for (int j = 0; j < 4; j++) {
        mma16816(c, f + 8 * j, a.qf[2 * j], a.qf[2 * j + 1]);
        mma16816(c + 4, f + 8 * j + 4, a.qf[2 * j], a.qf[2 * j + 1]);
    }
#pragma unroll
    for (int i = 0; i < 4; i++) s[i] = __uint_as_float((__float_as_uint(c[i]) & a.mv) | (__float_as_uint(c[i + 4]) & ~a.mv));
}
__device__ __forceinline__ void pv(Attn& a, const uint32_t* f, const uint32_t* b) {
#pragma unroll
    for (int j = 0; j < 4; j++) mma16816(a.o + 4 * j, f + 8 * j, b[0], b[1]);
#pragma unroll
    for (int j = 0; j < 4; j++) mma16816(a.o + 4 * j, f + 8 * j + 4, b[2], b[3]);
}
__device__ __forceinline__ void probs(Attn& a, float* y, uint32_t* b) {
#pragma unroll
    for (int i = 0; i < 4; i++) y[i] = ex2(y[i]);
    const uint32_t p0 = pack_bf16(y[0], y[1]), p1 = pack_bf16(y[2], y[3]);
    b[0] = movm(p0 & a.mv); b[1] = movm(p1 & a.mv);
    b[2] = movm(p0 & ~a.mv); b[3] = movm(p1 & ~a.mv);
    a.l0 += y[0] + y[2];
    a.l1 += y[1] + y[3];
    asm volatile("" : "+f"(a.l0), "+f"(a.l1));
}
__device__ __forceinline__ void softmax_step(Attn& a, float* s, uint32_t* b) {
    float y[4];
#pragma unroll
    for (int i = 0; i < 4; i++) s[i] += __shfl_xor_sync(FULL, s[i], 6);
#pragma unroll
    for (int i = 0; i < 4; i++) y[i] = fmaf(s[i], SCALE_LOG2E, (i & 1) ? a.n1 : a.n0);
    if (__any_sync(FULL, fmaxf(fmaxf(y[0], y[1]), fmaxf(y[2], y[3])) > MAX_SLACK)) {
        float t0 = fmaxf(s[0], s[2]), t1 = fmaxf(s[1], s[3]);
#pragma unroll
        for (int d = 4; d <= 16; d <<= 1) {
            t0 = fmaxf(t0, __shfl_xor_sync(FULL, t0, d));
            t1 = fmaxf(t1, __shfl_xor_sync(FULL, t1, d));
        }
        t0 = fminf(-SCALE_LOG2E * t0, a.n0); t1 = fminf(-SCALE_LOG2E * t1, a.n1);
        const float r0 = ex2(t0 - a.n0), r1 = ex2(t1 - a.n1);
        a.n0 = t0; a.n1 = t1;
        a.l0 *= r0; a.l1 *= r1;
#pragma unroll
        for (int i = 0; i < 16; i += 2) { a.o[i] *= r0; a.o[i + 1] *= r1; }
#pragma unroll
        for (int i = 0; i < 4; i++) y[i] = fmaf(s[i], SCALE_LOG2E, (i & 1) ? a.n1 : a.n0);
    }
    probs(a, y, b);
}

constexpr uint32_t NOPATCH = 0xff000000u, B80 = 0x80808080u, B87 = 0x87878787u;
__device__ __forceinline__ void lds4u(uint32_t* v, uint32_t a) { asm volatile("ld.shared.v4.u32 {%0,%1,%2,%3}, [%4];" : "=r"(v[0]), "=r"(v[1]), "=r"(v[2]), "=r"(v[3]) : "r"(a) : "memory"); }
__device__ __forceinline__ void sts4u(uint32_t a, const uint32_t* v) { asm volatile("st.shared.v4.u32 [%0], {%1,%2,%3,%4};" :: "r"(a), "r"(v[0]), "r"(v[1]), "r"(v[2]), "r"(v[3]) : "memory"); }
__device__ __forceinline__ void sts_u8(uint32_t a, uint32_t v) { asm volatile("st.shared.u8 [%0], %1;" :: "r"(a), "r"(v) : "memory"); }
__device__ __forceinline__ uint32_t lds_u16(uint32_t a) { uint32_t v; asm volatile("ld.shared.u16 %0, [%1];" : "=r"(v) : "r"(a) : "memory"); return v; }
__device__ __forceinline__ uint32_t bitsel(uint32_t a, uint32_t b, uint32_t m) {
    uint32_t d;
    asm("lop3.b32 %0, %1, %2, %3, 0xE4;" : "=r"(d) : "r"(a), "r"(b), "r"(m));
    return d;
}

__device__ __forceinline__ void pack_tile(uint32_t src, uint32_t dst, uint32_t meta, uint32_t id, uint32_t& patch, int lane) {
    src += lane * 16; dst += lane * 16;
    uint32_t m0 = 0, m1 = 0;
#pragma unroll
    for (int k = 0; k < 8; k++) {
        uint32_t r[4];
        lds4u(r, src + k * 512);
        asm("max.xorsign.abs.bf16x2 %0, %0, %1;" : "+r"(m0) : "r"(r[0]));
        asm("max.xorsign.abs.bf16x2 %0, %0, %1;" : "+r"(m1) : "r"(r[1]));
        asm("max.xorsign.abs.bf16x2 %0, %0, %1;" : "+r"(m0) : "r"(r[2]));
        asm("max.xorsign.abs.bf16x2 %0, %0, %1;" : "+r"(m1) : "r"(r[3]));
    }
    asm("max.xorsign.abs.bf16x2 %0, %0, %1;" : "+r"(m0) : "r"(m1));
    const int top = __reduce_max_sync(FULL, (int)max((m0 >> 24) & 0x7fu, (m0 >> 8) & 0x7fu));
    uint32_t base = max(top - 7, 0);
    const uint32_t base4 = base * 0x01010101u;
#pragma unroll 1
    for (int hf = 0; hf < 2; hf++) {
        uint32_t o[12], bad = 0;
#pragma unroll
        for (int k = 0; k < 4; k++) {
            uint32_t r[4];
            lds4u(r, src + hf * 2048 + k * 512);
            o[3 * k] = __byte_perm(r[0], r[1], 0x6420);
            o[3 * k + 1] = __byte_perm(r[2], r[3], 0x6420);
            const uint32_t h0 = __byte_perm(r[0], r[1], 0x7531), h1 = __byte_perm(r[2], r[3], 0x7531);
            const uint32_t u0 = (h0 | B80) - base4, u1 = (h1 | B80) - base4;
            if (((u0 ^ B80) | (u1 ^ B80)) & 0xf8f8f8f8u) bad |= 3u << (2 * k);
            const uint32_t x0 = bitsel(h0, u0, B80), x1 = bitsel(h1, u1, B80);
            o[3 * k + 2] = bitsel(x1, __funnelshift_l(x0, x0, 4), B87);
        }
        bad = __reduce_or_sync(FULL, bad);
#pragma unroll 1
        for (; bad != 0u && base != 0xffu; bad &= bad - 1u) {
            const int k = __ffs(bad) - 1;
            uint32_t r0, r1;
            const uint32_t at = hf * 2048 + (k >> 1) * 512 + (k & 1) * 8;
            asm volatile("ld.shared.v2.u32 {%0,%1}, [%2];" : "=r"(r0), "=r"(r1) : "r"(src + at) : "memory");
            const uint32_t hh = __byte_perm(r0, r1, 0x7531);
            uint32_t b = (((hh | B80) - base4) ^ B80) & 0xf8f8f8f8u;
#pragma unroll 1
            for (uint32_t lanes; (lanes = __ballot_sync(FULL, b != 0u)) != 0u;) {
                const int n = __popc(__ballot_sync(FULL, patch != NOPATCH));
                if (n == 32) {
                    base = 0xffu;
                    if ((patch >> 24) == id) patch = NOPATCH;
                    break;
                }
                const int i = (__ffs(b) - 1) >> 3, from = __ffs(lanes) - 1;
                const uint32_t ent = __shfl_sync(FULL, (id << 24) | ((at + lane * 16 + 2 * i + 1) << 8) | ((hh >> (8 * i)) & 0xffu), from);
                if (lane == n) patch = ent;
                if (lane == from) b &= ~(0xffu << (8 * i));
            }
        }
#pragma unroll
        for (int j = 0; j < 3; j++) sts4u(dst + hf * 1536 + j * 512, o + 4 * j);
    }
    if (lane == 0) sts_u8(meta, base);
}
__device__ __forceinline__ void unpack_tile(const uint32_t* o, uint32_t dst, uint32_t base4) {
#pragma unroll
    for (int k = 0; k < 8; k++) {
        const uint32_t n = o[3 * k + 2];
        const uint32_t h0 = (__funnelshift_r(n, n, 4) & B87) + base4, h1 = (n & B87) + base4;
        uint32_t r[4];
        r[0] = __byte_perm(o[3 * k], h0, 0x5140); r[1] = __byte_perm(o[3 * k], h0, 0x7362);
        r[2] = __byte_perm(o[3 * k + 1], h1, 0x5140); r[3] = __byte_perm(o[3 * k + 1], h1, 0x7362);
        sts4u(dst + k * 512, r);
    }
}

__device__ __forceinline__ uint32_t add_residual(uint32_t xp, const uint32_t (*v)[4], bool half) {
    float r[4];
#pragma unroll
    for (int k = 0; k < 4; k++)
        r[k] = (__uint_as_float(v[0][k]) + __uint_as_float(v[1][k])) + (__uint_as_float(v[2][k]) + __uint_as_float(v[3][k]));
    const float y0 = selp(r[2], r[0], half) + __shfl_xor_sync(FULL, selp(r[0], r[2], half), 16);
    const float y1 = selp(r[3], r[1], half) + __shfl_xor_sync(FULL, selp(r[1], r[3], half), 16);
    const uint32_t yb = pack_bf16(y0, y1);
    return pack_bf16(bf_lo(xp) + bf_lo(yb), bf_hi(xp) + bf_hi(yb));
}

__device__ __forceinline__ void gemv_load(uint32_t (*f)[4], uint32_t tile, int lane) {
    const int mi = lane >> 3, r = lane & 7;
    const uint32_t a0 = tile + ((mi >> 1) * 8 + r) * 64 + (((mi & 1) ^ (r >> 1)) << 4);
#pragma unroll
    for (int j = 0; j < 4; j++) {
        ldsm4t(f[2 * j], a0 + j * 1024);
        ldsm4t(f[2 * j + 1], (a0 ^ 32u) + j * 1024);
    }
}
template <bool STATS>
__device__ __forceinline__ void gemv_mma(const uint32_t (*f)[4], uint32_t vpair, float& y0, float& y1, float* st, int lane) {
    const int src = ((lane >> 1) & 1) + 16 * (lane & 1);
    float c[4][4];
    uint32_t x[8];
#pragma unroll
    for (int j = 0; j < 8; j++) x[j] = __shfl_sync(FULL, vpair, 2 * j + src);
#pragma unroll
    for (int i = 0; i < 4; i++) { c[0][i] = c[1][i] = c[2][i] = c[3][i] = 0.f; if (STATS) st[i] = 0.f; }
#pragma unroll
    for (int j = 0; j < 4; j++) {
        uint32_t b0 = x[2 * j], b1 = x[2 * j + 1];
        if (STATS && (lane & 4)) b0 = b1 = 0x3f803f80u;
        mma16816(c[2 * (j & 1)], f[2 * j], b0, b1);
        mma16816(c[2 * (j & 1) + 1], f[2 * j + 1], b0, b1);
        if (STATS) mma16816(st, x[2 * j], x[2 * j], x[2 * j + 1], x[2 * j + 1], b0, b1);
    }
    const bool t1 = lane & 1, t2 = lane & 2;
    y0 = selp(selp(c[1][2] + c[3][2], c[1][0] + c[3][0], t1), selp(c[0][2] + c[2][2], c[0][0] + c[2][0], t1), t2);
    if (STATS) y1 = selp(selp(c[1][3] + c[3][3], c[1][1] + c[3][1], t1), selp(c[0][3] + c[2][3], c[0][1] + c[2][1], t1), t2);
}

__global__ void __launch_bounds__(NW * 32, 1)
decode_kernel(const __grid_constant__ Params p) {
    extern __shared__ __align__(1024) unsigned char smem_raw[];
    const uint32_t smem = (uint32_t)__cvta_generic_to_shared(smem_raw);
    int lane = lane_id();
    const int w = __shfl_sync(FULL, threadIdx.x >> 5, 0);
    const int cta = blockIdx.x, h = cta >> 4;
    const uint32_t wslots = smem + w * (NSLOT * TILE);
    const uint32_t wbars = smem + OFF_BAR + w * (NSLOT * 8);
    TSTAMP(0);
    if (lane < NSLOT) {
        asm volatile("mbarrier.init.shared::cta.b64 [%0], 1;" :: "r"(wbars + lane * 8) : "memory");
        asm volatile("fence.proxy.async.shared::cta;" ::: "memory");
    }
    __syncwarp();
    refill(p, 16 | (M_WQA << 6), wslots, wbars, w);
#pragma unroll
    for (int i = 1; i < NFIRST; i++) refill(p, (i << 16) | 16 | (((i - 1) & 1) << 6) | (((i - 1) >> 1) << 9), wslots, wbars, w);
    uint32_t xp = reinterpret_cast<const uint32_t*>(p.x)[32 * w + 2 * (lane & 15) + (lane >> 4)];
    TSTAMP(1);

    uint32_t rf[2 * NRF][24];
    uint32_t patch = NOPATCH;
#pragma unroll
    for (int i = 0; i < 2 * NRF; i++)
#pragma unroll
        for (int j = 0; j < 24; j++) rf[i][j] = 0u;

#pragma unroll 1
    for (int layer = 0; layer < 4; layer++) {
        const uint32_t tag = (layer + 1) & 3;
        int c = p.first[layer];
        Attn a;
        {
            const uint32_t e = p.steps[c];
            const int half = lane >> 4;
            const uint32_t ptag = layer & 3;
            const float* src = pin(&p.xc->x[(layer + 1) & 1][16 * half + 2 * w][4 * (lane & 15)]);
            uint32_t v[4][4], f[8][4];
            if (layer > 0) {
#pragma unroll
                for (int j = 0; j < 4; j++) ld_rlx16(v[j], src + j * 1024);
            } else {
#pragma unroll
                for (int j = 0; j < 4; j++) v[j][0] = v[j][1] = v[j][2] = v[j][3] = 0u;
            }
            wait_step(wbars, e);
            gemv_load(f, slot_addr(wslots, e), lane);
            asm volatile("" :: "r"(f[7][3]), "r"(f[6][3]) : "memory");
            refill_if(p, e, wslots, wbars, w);
            if (layer > 0) {
                int it = 0;
                while (!__all_sync(FULL, (((v[0][0] ^ ptag) | (v[1][0] ^ ptag) | (v[2][0] ^ ptag) | (v[3][0] ^ ptag)) & 3u) == 0u) && ++it < SPIN_LIMIT) {
#pragma unroll
                    for (int j = 0; j < 4; j++)
                        if ((v[j][0] ^ ptag) & 3u) ld_rlx16(v[j], src + j * 1024);
                }
                xp = add_residual(xp, v, half);
                TSTAMP(layer * 8);
            }
            refill_if(p, p.steps[c + 1], wslots, wbars, w);
            float y0, y1, st[4];
            gemv_mma<true>(f, xp, y0, y1, st, lane);
            float* dst = pin(&p.xc->q[cta][2 * lane]);
            sts2(smem + OFF_RED + w * 256 + (8 * (lane & 3) + (lane >> 2)) * 8, y0, y1);
            if (lane == 0) sts2(smem + OFF_ST + w * 8, st[0], st[1]);
            __syncthreads();
            if (w == 0) {
                float u[8][4], z[16];
#pragma unroll
                for (int i = 0; i < 4; i++) lds4(z + 4 * i, smem + OFF_ST + 16 * i);
#pragma unroll
                for (int i = 0; i < 8; i++) lds4(u[i], smem + OFF_RED + i * 256 + (lane & 15) * 16);
                const float sq = ((z[0] + z[2]) + (z[4] + z[6])) + ((z[8] + z[10]) + (z[12] + z[14]));
                const float su = ((z[1] + z[3]) + (z[5] + z[7])) + ((z[9] + z[11]) + (z[13] + z[15]));
                const float mean = su * (1.f / 512.f);
                const float rstd = rsq(fmaxf(fmaf(-mean, mean, sq * (1.f / 512.f)), 0.f) + 1e-5f);
                float r[4];
#pragma unroll
                for (int k = 0; k < 4; k++) r[k] = ((u[0][k] + u[1][k]) + (u[2][k] + u[3][k])) + ((u[4][k] + u[5][k]) + (u[6][k] + u[7][k]));
                if (lane < 16) st_rlx8(dst, tagged(fmaf(-mean, r[1], r[0]) * rstd, tag), __float_as_uint(fmaf(-mean, r[3], r[2]) * rstd));
            }
            TSTAMP(2 + layer * 8);
            refill_if(p, p.steps[c + 2], wslots, wbars, w);
            refill_if(p, p.steps[c + 3], wslots, wbars, w);
            c += 4;
            __syncthreads();
        }
        const uint32_t offk = (((lane >> 3) & 1) * 8 + (lane & 7)) * 128 + ((((lane >> 4) & 1) ^ (lane & 7)) << 4);
        const uint32_t offv = (((lane >> 4) & 1) * 8 + (lane & 7)) * 128 + ((((lane >> 3) & 1) ^ (lane & 7)) << 4);
        a.mv = pin((((lane >> 2) ^ (lane >> 1)) & 1) - 1u);
        uint32_t f[32];
        if (layer & 1) {
            const uint32_t e = p.steps[c];
            wait_step(wbars, e);
            load_k(f, slot_addr(wslots, e) + offk);
            asm volatile("" :: "r"(f[31]), "r"(f[27]) : "memory");
            refill_if(p, e, wslots, wbars, w);
        } else {
#pragma unroll
            for (int i = 0; i < 32; i++) f[i] = 0u;
        }
        {
            const float* qsrc = pin(&p.xc->q[h * 16 + 2 * w][2 * lane]);
            const uint32_t qd = pin(smem + OFF_RED + ((lane >> 4) * 32 + 4 * ((w >> 1) + 4 * (w & 1)) + (lane & 3)) * 16 + (lane & 12));
            uint32_t v0, v1;
            int it = 0;
            do { ld_rlx8(v0, v1, qsrc); } while (!__all_sync(FULL, ((v0 ^ tag) & 3u) == 0u) && ++it < SPIN_LIMIT);
            sts(qd, __uint_as_float(pack_bf16(__uint_as_float(v0), __uint_as_float(v1))));
            __syncthreads();
            lds4(reinterpret_cast<float*>(a.qf), smem + OFF_RED + lane * 16);
            lds4(reinterpret_cast<float*>(a.qf + 4), smem + OFF_RED + 512 + lane * 16);
        }
        TSTAMP(3 + layer * 8);
        if (layer & 1) {
            const uint32_t ek1 = p.steps[c + 1], ev0 = p.steps[c + 2], ev = p.steps[c + 3];
            uint32_t b[8];
            float s[8];
            qk(a, f, s);
            wait_step(wbars, ek1);
            load_k(f, slot_addr(wslots, ek1) + offk);
            qk(a, f, s + 4);
            refill(p, ek1, wslots, wbars, w);
#pragma unroll
            for (int i = 0; i < 8; i++) s[i] += __shfl_xor_sync(FULL, s[i], 6);
            float t0 = fmaxf(fmaxf(s[0], s[2]), fmaxf(s[4], s[6])), t1 = fmaxf(fmaxf(s[1], s[3]), fmaxf(s[5], s[7]));
#pragma unroll
            for (int d = 4; d <= 16; d <<= 1) {
                t0 = fmaxf(t0, __shfl_xor_sync(FULL, t0, d));
                t1 = fmaxf(t1, __shfl_xor_sync(FULL, t1, d));
            }
            a.n0 = -SCALE_LOG2E * t0; a.n1 = -SCALE_LOG2E * t1;
            a.l0 = a.l1 = 0.f;
#pragma unroll
            for (int i = 0; i < 8; i++) s[i] = fmaf(s[i], SCALE_LOG2E, (i & 1) ? a.n1 : a.n0);
            wait_step(wbars, ev0);
            load_v(f, slot_addr(wslots, ev0) + offv);
            probs(a, s, b);
            probs(a, s + 4, b + 4);
#pragma unroll
            for (int i = 0; i < 16; i++) a.o[i] = 0.f;
            pv(a, f, b);
            refill(p, ev0, wslots, wbars, w);
            wait_step(wbars, ev);
            load_v(f, slot_addr(wslots, ev) + offv);
            pv(a, f, b + 4);
        } else {
#pragma unroll
            for (int i = 0; i < 16; i++) a.o[i] = 0.f;
            a.n0 = a.n1 = INFINITY;
            a.l0 = a.l1 = 0.f;
#pragma unroll 1
            for (;;) {
                float s[4];
                uint32_t b[4];
                const uint32_t ek = p.steps[c++];
                const uint32_t ev = p.steps[c++];
                if ((ek & STEP_RF) && layer == 2) {
                    const uint32_t r = (ek >> 21) & 3u;
                    const uint32_t bb = lds_u16(smem + OFF_META + w * 16 + 2 * r), l16 = lane_id() * 16;
                    const uint32_t ak = slot_addr(wslots, ek), av = slot_addr(wslots, ev);
                    const uint32_t bk = __byte_perm(bb, 0, 0x0000), bv = __byte_perm(bb, 0, 0x1111);
#pragma unroll
                    for (int i = 0; i < NRF; i++) if (r == i) {
                        unpack_tile(rf[2 * i], ak + l16, bk);
                        unpack_tile(rf[2 * i + 1], av + l16, bv);
                    }
                    __syncwarp();
                    if ((patch >> 25) == r) sts_u8(((patch >> 24) & 1u ? av : ak) + ((patch >> 8) & 0xfffu), patch);
                    asm volatile("fence.proxy.async.shared::cta;" ::: "memory");
                    const uint32_t again = __ballot_sync(FULL, (lane_id() & 1 ? bv : bk) == 0xffffffffu) & 3u;
                    asm volatile("{\n.reg .pred p, q;\nelect.sync _|p, 0xffffffff;\n"
                                 "setp.eq.and.u32 q, %2, 0, p;\n@q mbarrier.arrive.shared::cta.b64 _, [%0];\n"
                                 "setp.eq.and.u32 q, %3, 0, p;\n@q mbarrier.arrive.shared::cta.b64 _, [%1];\n}"
                                 :: "r"(slot_bar(wbars, ek)), "r"(slot_bar(wbars, ev)), "r"(again & 1u), "r"(again & 2u) : "memory");
                    if (again) {
                        refill(p, ((again & 1u) << 4) | (r << 9) | ((ek & 7u) << 16), wslots, wbars, w);
                        refill(p, ((again & 2u) << 3) | (1 << 6) | (r << 9) | ((ev & 7u) << 16), wslots, wbars, w);
                    }
                }
                wait_step(wbars, ek);
                load_k(f, slot_addr(wslots, ek) + offk);
                qk(a, f, s);
                refill(p, ek, wslots, wbars, w);
                softmax_step(a, s, b);
                wait_step(wbars, ev);
                load_v(f, slot_addr(wslots, ev) + offv);
                pv(a, f, b);
                refill(p, ev, wslots, wbars, w);
                if ((ek & STEP_RF) && layer == 0) {
                    const uint32_t r = (ek >> 21) & 3u;
                    const int ln = lane_id();
                    __syncwarp();
#pragma unroll 1
                    for (int i = 0; i < 2; i++) {
                        const uint32_t at = slot_addr(wslots, i ? ev : ek);
                        pack_tile(at, at, smem + OFF_META + w * 16 + 2 * r + i, 2 * r + i, patch, ln);
                    }
                    const uint32_t l16 = ln * 16;
                    const uint32_t ak = slot_addr(wslots, ek) + l16, av = slot_addr(wslots, ev) + l16;
#pragma unroll
                    for (int i = 0; i < NRF; i++) if (r == i) {
#pragma unroll
                        for (int j = 0; j < 6; j++) { lds4u(&rf[2 * i][4 * j], ak + j * 512); lds4u(&rf[2 * i + 1][4 * j], av + j * 512); }
                    }
                    asm volatile("fence.proxy.async.shared::cta;" ::: "memory");
                    __syncwarp();
                }
                if (ev & STEP_LAST) break;
            }
        }
        c = p.last[layer] + 1;
        const uint32_t ev = p.steps[c++];
        lane = lane_id();
        const int g = lane >> 2, t = lane & 3, half = lane >> 4, c16 = lane & 15;
        TSTAMP(4 + layer * 8);
        uint32_t v[8][4], mj, lj;
        const float* src = pin(&p.xc->part[h * 16 + half][w][4 * c16]);
        const float* ssrc = pin(&p.xc->part[h * 16 + c16][w][64]);
        {
            a.l0 += __shfl_xor_sync(FULL, a.l0, 4);
            a.l1 += __shfl_xor_sync(FULL, a.l1, 4);
            a.l0 += __shfl_xor_sync(FULL, a.l0, 8);
            a.l1 += __shfl_xor_sync(FULL, a.l1, 8);
            const uint32_t o0 = slot_addr(wslots, ev) + ((4 * (t & 1) + (t >> 1)) * 96 + 8 * t + g) * 4;
#pragma unroll
            for (int i = 0; i < 4; i++) {
                sts(o0 + i * 64, a.o[4 * i]);
                sts(o0 + i * 64 + 192 * 4, a.o[4 * i + 1]);
                sts(o0 + i * 64 + 32, a.o[4 * i + 2]);
                sts(o0 + i * 64 + 192 * 4 + 32, a.o[4 * i + 3]);
            }
            a.l0 += __shfl_xor_sync(FULL, a.l0, 16);
            a.l1 += __shfl_xor_sync(FULL, a.l1, 16);
            if (lane < 2) {
                const uint32_t ml = smem + OFF_ML + lane * 128 + w * 4;
                sts(ml, -a.n0); sts(ml + 64, -a.n1); sts(ml + 32, a.l0); sts(ml + 96, a.l1);
            }
            float* dst = pin(&p.xc->part[cta][w][4 * lane]);
            const uint32_t mlr = pin(smem + OFF_ML + (w >> 1) * 64 + half * 16);
            const uint32_t ro = pin(slot_addr(smem, ev) + half * (4 * NSLOT * TILE) + (w * 96 + 8 * ((w >> 2) + 2 * (w & 1)) + 4 * c16) * 4);
            __syncthreads();
            float m[8], l[4], u[4][4];
            lds4(m, mlr);
            lds4(m + 4, mlr ^ 16u);
#pragma unroll
            for (int i = 0; i < 4; i++) lds4(u[i], ro + i * (NSLOT * TILE));
            lds4(l, mlr + 32);
            const float M = fmaxf(fmaxf(fmaxf(m[0], m[1]), fmaxf(m[2], m[3])), fmaxf(fmaxf(m[4], m[5]), fmaxf(m[6], m[7])));
            float z[4], r[4];
#pragma unroll
            for (int i = 0; i < 4; i++) z[i] = ex2(m[i] - M);
#pragma unroll
            for (int k = 0; k < 4; k++) r[k] = fmaf(z[0], u[0][k], z[1] * u[1][k]) + fmaf(z[2], u[2][k], z[3] * u[3][k]);
            float L = fmaf(z[0], l[0], z[1] * l[1]) + fmaf(z[2], l[2], z[3] * l[3]);
#pragma unroll
            for (int k = 0; k < 4; k++) r[k] += __shfl_xor_sync(FULL, r[k], 16);
            L += __shfl_xor_sync(FULL, L, 16);
            if (lane <= 16) st_rlx16(dst, tagged(selp(M, r[0], half), tag), __float_as_uint(selp(L, r[1], half)), __float_as_uint(r[2]), __float_as_uint(r[3]));
            TSTAMP(5 + layer * 8);
            ld_rlx8(mj, lj, ssrc);
#pragma unroll
            for (int j = 0; j < 8; j++) ld_rlx16(v[j], src + j * (2 * NW * 96));
            asm volatile("fence.proxy.async.shared::cta;" ::: "memory");
            __syncthreads();
            refill_if(p, ev, wslots, wbars, w);
            refill_if(p, p.steps[c], wslots, wbars, w);
        }
        {
            const uint32_t e = p.steps[c + 1];
            int it = 0;
            for (;;) {
                uint32_t bad = mj ^ tag;
#pragma unroll
                for (int j = 0; j < 8; j++) bad |= v[j][0] ^ tag;
                if (__all_sync(FULL, (bad & 3u) == 0u) || ++it >= SPIN_LIMIT) break;
                if ((mj ^ tag) & 3u) ld_rlx8(mj, lj, ssrc);
#pragma unroll
                for (int j = 0; j < 8; j++)
                    if ((v[j][0] ^ tag) & 3u) ld_rlx16(v[j], src + j * (2 * NW * 96));
            }
            TSTAMP(6 + layer * 8);
            const int key = (int)mj ^ (((int)mj >> 31) & 0x7fffffff);
            const int kmax = __reduce_max_sync(FULL, key);
            const float M = __int_as_float(kmax ^ ((kmax >> 31) & 0x7fffffff));
            const float fo = ex2(__uint_as_float(mj) - M);
            float fj[8], r[4];
#pragma unroll
            for (int j = 0; j < 8; j++) fj[j] = __shfl_sync(FULL, fo, 2 * j + half);
#pragma unroll
            for (int k = 0; k < 4; k++) {
                float r0 = fj[0] * __uint_as_float(v[0][k]), r1 = fj[1] * __uint_as_float(v[1][k]);
#pragma unroll
                for (int j = 2; j < 8; j += 2) { r0 = fmaf(fj[j], __uint_as_float(v[j][k]), r0); r1 = fmaf(fj[j + 1], __uint_as_float(v[j + 1][k]), r1); }
                r[k] = r0 + r1;
            }
            const float y0 = selp(r[2], r[0], half) + __shfl_xor_sync(FULL, selp(r[0], r[2], half), 16);
            const float y1 = selp(r[3], r[1], half) + __shfl_xor_sync(FULL, selp(r[1], r[3], half), 16);
            refill_if(p, p.steps[c + 2], wslots, wbars, w);
            wait_step(wbars, e);
            uint32_t fw[8][4];
            gemv_load(fw, slot_addr(wslots, e), lane);
            float L = fo * __uint_as_float(lj);
#pragma unroll
            for (int d = 1; d < 16; d <<= 1) L += __shfl_xor_sync(FULL, L, d);
            float y, unused;
            gemv_mma<false>(fw, pack_bf16(y0, y1), y, unused, nullptr, lane);
            float* dst = pin(&p.xc->x[layer & 1][cta][4 * lane]);
            sts(smem + OFF_RED + w * 128 + (8 * t + g) * 4, y * rcp(L));
            __syncthreads();
            if (w == 0) {
                float u[8][4];
#pragma unroll
                for (int i = 0; i < 8; i++) lds4(u[i], smem + OFF_RED + i * 128 + (lane & 7) * 16);
#pragma unroll
                for (int k = 0; k < 4; k++) r[k] = ((u[0][k] + u[1][k]) + (u[2][k] + u[3][k])) + ((u[4][k] + u[5][k]) + (u[6][k] + u[7][k]));
                if (lane < 8) st_rlx16(dst, tagged(r[0], tag), __float_as_uint(r[1]), __float_as_uint(r[2]), __float_as_uint(r[3]));
            }
            TSTAMP(7 + layer * 8);
            refill_if(p, e, wslots, wbars, w);
            refill_if(p, p.steps[c + 3], wslots, wbars, w);
            __syncthreads();
        }
    }
    if (cta == 0) {
        const float* src = &p.xc->x[1][16 * (lane >> 4) + 2 * w][4 * (lane & 15)];
        uint32_t v[4][4];
        int it = 0;
        do {
#pragma unroll
            for (int j = 0; j < 4; j++) ld_rlx16(v[j], src + j * 1024);
        } while (!__all_sync(FULL, ((v[0][0] | v[1][0] | v[2][0] | v[3][0]) & 3u) == 0u) && ++it < SPIN_LIMIT);
        reinterpret_cast<uint32_t*>(p.out)[32 * w + 2 * (lane & 15) + (lane >> 4)] = add_residual(xp, v, lane >> 4);
        TSTAMP(32);
    }
}

typedef CUresult (*EncodeFn)(CUtensorMap*, CUtensorMapDataType, cuuint32_t, void*, const cuuint64_t*, const cuuint64_t*,
                             const cuuint32_t*, const cuuint32_t*, CUtensorMapInterleave, CUtensorMapSwizzle,
                             CUtensorMapL2promotion, CUtensorMapFloatOOBfill);

void encode5d(EncodeFn enc, CUtensorMap* m, const void* ptr, uint32_t cols, uint32_t rows, uint32_t nchunk,
              uint64_t srow, uint64_t schunk, uint64_t ss, uint64_t sh, CUtensorMapSwizzle sw, CUtensorMapL2promotion promo) {
    cuuint64_t dims[5] = {cols, rows, nchunk, 16, 8};
    cuuint64_t strides[4] = {srow, schunk, ss, sh};
    cuuint32_t box[5] = {cols, rows, 1, 1, 1};
    cuuint32_t es[5] = {1, 1, 1, 1, 1};
    CUresult r = enc(m, CU_TENSOR_MAP_DATA_TYPE_BFLOAT16, 5, const_cast<void*>(ptr), dims, strides, box, es,
        CU_TENSOR_MAP_INTERLEAVE_NONE, sw, promo, CU_TENSOR_MAP_FLOAT_OOB_FILL_NONE);
    (void)r;
}

struct Sched {
    unsigned long long ord1 = 0x07251893ab4cdef6;
    unsigned long long ord3 = 0x469c1573e2ad08bf;
    unsigned long long l2 = 0xfffd4000;
    int parkat = 14;
    int nearly = 2;
    int promoB = 0;
    int promoW = 0;
    int d0 = 4;
    int dr = 3;
    int d1 = 2;
    int d3 = 5;
    int ch1 = 111111111, ch2 = 111101100, ch3 = 333244353;
    int pf1 = 100000000, pf2 = 100000000;
};

void build_schedule(Params& p, const Sched& sc) {
    struct Item { int map, tile, promote, park; };
    Item items[96];
    int n = 0;
    auto add = [&](int map, int tile, int promote, int park = 0) { items[n] = Item{map, tile, promote, park}; return n++; };
    auto dig = [](int v, int i) { for (int k = 8; k > i; k--) v /= 10; return v % 10; };
    int c1[32], n1 = 0, c3[32], n3 = 0;
    const int lp = NRF + 2, nearly = 2 * sc.nearly;
    const bool late = true;
    const int wq1 = add(M_WQA, 0, 0);
    int vlate = -1;
    for (int sp = 0; sp < 16; sp++) {
        const int pr = (sc.ord1 >> (60 - 4 * sp)) & 15;
        if (sp == sc.parkat) vlate = add(1, lp, 0, 1);
        c1[n1++] = add(0, pr, (sc.l2 >> (2 * pr)) & 1);
        c1[n1++] = pr == lp ? vlate : add(1, pr, (sc.l2 >> (2 * pr + 1)) & 1);
    }
    auto tile_of = [&](int it) { return 2 * items[it].tile + items[it].map; };
    auto keep1 = [&](int it) { return items[it].tile >= NRF && items[it].tile <= lp; };
    const int tail1 = n;
    add(M_WOA, 0, sc.promoW & 1);
    add(M_WQB, 0, sc.promoB & 1);
    for (int u = 0; u < 4; u++) add(M_KB + (u >> 1), u & 1, (sc.promoB >> (1 + u)) & 1);
    add(M_WOB, 0, (sc.promoB >> 5) & 1);
    add(M_WQA, 0, 0);
    for (int sp = 0; sp < 16; sp++) {
        const int pr = (sc.ord3 >> (60 - 4 * sp)) & 15;
        for (int u = 2 * pr; u < 2 * pr + 2; u++) {
            int it = -1;
            for (int i = 0; i < n1; i++) if (keep1(c1[i]) && tile_of(c1[i]) == u) it = c1[i];
            c3[n3++] = pr < NRF ? -1 - u : (it >= 0 ? it : add(u & 1, u >> 1, 0));
        }
    }
    const int tail3 = n;
    add(M_WOA, 0, 0); add(M_WQB, 0, 0);
    for (int u = 0; u < 4; u++) add(M_KB + (u >> 1), u & 1, 0);
    add(M_WOB, 0, 0);
    int slot_of[96], pending[96] = {0}, fre[16], nfree = 0, par[NSLOT] = {0}, ic = NFIRST, c = 0, nq = NFIRST, reserve = 0;
    for (int i = 0; i < NFIRST; i++) { slot_of[i] = i; pending[i] = 1; }
    for (int i = NSLOT - 1; i >= NFIRST; i--) fre[nfree++] = i;
    for (int i = 0; i < NSTEP; i++) p.steps[i] = 0;
    auto load = [&](int depth) -> uint32_t {
        if (!(ic < n && nfree > reserve && nq < depth)) return 0;
        const Item& it = items[ic];
        const int dst = slot_of[ic] = fre[--nfree];
        if (!it.park) { pending[ic] = 1; nq++; }
        ic++;
        return 16 | (it.promote << 5) | (it.map << 6) | (it.tile << 9) | (dst << 16);
    };
    int pc = 0, pfd = 0;
    auto load_or_pf = [&](int depth) -> uint32_t {
        uint32_t e = load(depth);
        if (pc < ic) pc = ic;
        if (!e && pc < n && nq + (pc - ic) < pfd) { e = 32 | (items[pc].map << 6) | (items[pc].tile << 9); pc++; }
        return e;
    };
    auto extra = [&](int depth) { p.steps[c++] = load_or_pf(depth); };
    auto release = [&](int slot) { par[slot] ^= 1; fre[nfree++] = slot; };
    auto consume = [&](int it, bool keep) -> uint32_t {
        const int slot = slot_of[it];
        if (pending[it]) { pending[it] = 0; nq--; }
        const uint32_t e = slot | (par[slot] << 3);
        if (!keep) release(slot);
        return e;
    };
    auto step = [&](int it, bool keep, int depth) { const uint32_t e = consume(it, keep); p.steps[c++] = e | load_or_pf(depth); };
    auto atleast1 = [](int d) { return d < 1 ? 1 : d; };
    int layer = 0;
    auto chain = [&](int t0, bool keep0, int t1, bool keep1_, int wo, int wq, int d, int pf) {
        reserve = keep1_ ? 1 : 0;
        pfd = dig(pf, 0) - 1;
        step(t0, keep0, atleast1(dig(d, 0)));
        reserve = 0;
        p.steps[c++] = consume(t1, keep1_) | STEP_LAST;
        p.last[layer++] = c - 1;
        const int scratch = fre[nfree - 1];
        pfd = dig(pf, 1);
        extra(atleast1(dig(d, 1))); p.steps[c - 1] |= scratch;
        extra(dig(d, 1));
        const int at = c++;
        pfd = dig(pf, 2);
        extra(dig(d, 2));
        p.steps[at] = consume(wo, false);
        pfd = dig(pf, 3);
        p.steps[at] |= load_or_pf(atleast1(dig(d, 3)));
        extra(dig(d, 3));
        if (wq < 0) return;
        p.first[layer] = c;
        pfd = dig(pf, 4);
        step(wq, false, dig(d, 4));
        pfd = dig(pf, 5);
        extra(dig(d, 5));
        pfd = dig(pf, 6);
        extra(atleast1(dig(d, 6))); extra(dig(d, 6));
        pfd = 0;
    };
    p.first[0] = 0;
    step(wq1, false, 0); extra(0); extra(sc.d0); extra(sc.d0);
    for (int u = 0; u < 30; u++) {
        if (late && u == 29) { reserve = 1; pfd = dig(sc.pf1, 0) - 1; }
        const int depth = u < 2 ? sc.d0 : (u < nearly ? sc.dr : sc.d1), pr = items[c1[u]].tile;
        if (pr < NRF) {
            step(c1[u], true, depth);
            if (u & 1) { release(slot_of[c1[u - 1]]); release(slot_of[c1[u]]); } else p.steps[c - 1] |= STEP_RF | (pr << 21);
        } else step(c1[u], keep1(c1[u]), depth);
    }
    chain(c1[30], keep1(c1[30]), c1[31], keep1(c1[31]), tail1, tail1 + 1, sc.ch1, sc.pf1);
    step(tail1 + 2, false, atleast1(dig(sc.ch1, 7))); step(tail1 + 3, false, atleast1(dig(sc.ch1, 8)));
    chain(tail1 + 4, false, tail1 + 5, false, tail1 + 6, tail1 + 7, sc.ch2, sc.pf2);
    for (int u = 0; u < n3 - 2; u++) {
        int left = 0;
        for (int i = u + 1; i < n3; i++) left += c3[i] >= 0;
        const int cap = left + dig(sc.ch3, 0) - 1, depth = sc.d3 < cap ? sc.d3 : cap;
        const int nxt = (u | 1) + 1;
        reserve = nxt < n3 && c3[nxt] < 0 ? ((u & 1) ? 2 : 1) : 0;
        if (c3[u] < 0) {
            const int sk = fre[--nfree], sv = fre[--nfree];
            uint32_t e = sk | (par[sk] << 3) | STEP_RF | (((-1 - c3[u]) >> 1) << 21);
            release(sk); p.steps[c++] = e | load(depth);
            u++;
            reserve = nxt < n3 && c3[nxt] < 0 ? 2 : 0;
            e = sv | (par[sv] << 3);
            release(sv); p.steps[c++] = e | load(depth);
        } else step(c3[u], false, depth);
    }
    reserve = 0;
    chain(c3[n3 - 2], false, c3[n3 - 1], false, tail3, tail3 + 1, sc.ch3, 0);
    step(tail3 + 2, false, atleast1(dig(sc.ch3, 7))); step(tail3 + 3, false, atleast1(dig(sc.ch3, 8)));
    chain(tail3 + 4, false, tail3 + 5, false, tail3 + 6, -1, 777777777, 0);
}

Sched g_sched;

}

extern "C" void kernel_launch(void* const* d_in, const int* in_sizes, int n_in, void* d_out, int out_size) {
    (void)in_sizes; (void)n_in; (void)out_size;
    void* fn = nullptr;
    cudaDriverEntryPointQueryResult qr;
    cudaGetDriverEntryPoint("cuTensorMapEncodeTiled", &fn, cudaEnableDefault, &qr);
    EncodeFn enc = (EncodeFn)fn;
    Params p;
    const CUtensorMapL2promotion pk = CU_TENSOR_MAP_L2_PROMOTION_L2_256B, pw = CU_TENSOR_MAP_L2_PROMOTION_NONE;
    const size_t win = (size_t)28672 * 256;
    encode5d(enc, &p.maps[M_KA], d_in[1], 64, 32, 128, 128, 4096, 512 << 10, 8 << 20, CU_TENSOR_MAP_SWIZZLE_128B, pk);
    encode5d(enc, &p.maps[M_VA], d_in[2], 64, 32, 128, 128, 4096, 512 << 10, 8 << 20, CU_TENSOR_MAP_SWIZZLE_128B, pk);
    encode5d(enc, &p.maps[M_KB], (const char*)d_in[6] + win, 64, 32, 16, 128, 4096, 64 << 10, 8 << 20, CU_TENSOR_MAP_SWIZZLE_128B, pk);
    encode5d(enc, &p.maps[M_VB], (const char*)d_in[7] + win, 64, 32, 16, 128, 4096, 64 << 10, 8 << 20, CU_TENSOR_MAP_SWIZZLE_128B, pk);
    encode5d(enc, &p.maps[M_WQA], d_in[3], 32, 64, 8, 8192, 64 * 8192, 64, 1024, CU_TENSOR_MAP_SWIZZLE_64B, pw);
    encode5d(enc, &p.maps[M_WQB], d_in[8], 32, 64, 8, 8192, 64 * 8192, 64, 1024, CU_TENSOR_MAP_SWIZZLE_64B, pw);
    encode5d(enc, &p.maps[M_WOA], d_in[4], 32, 64, 8, 1024, 64 << 10, 64, 512 << 10, CU_TENSOR_MAP_SWIZZLE_64B, pw);
    encode5d(enc, &p.maps[M_WOB], d_in[9], 32, 64, 8, 1024, 64 << 10, 64, 512 << 10, CU_TENSOR_MAP_SWIZZLE_64B, pw);
    void* xc = nullptr;
    cudaGetSymbolAddress(&xc, g_xchg);
    p.xc = (Xchg*)xc;
    p.x = (const __nv_bfloat16*)d_in[0];
    p.out = (__nv_bfloat16*)d_out;
    build_schedule(p, g_sched);
    cudaFuncSetAttribute(decode_kernel, cudaFuncAttributeMaxDynamicSharedMemorySize, SMEM_BYTES);
    decode_kernel<<<NCTA, NW * 32, SMEM_BYTES, cudaStreamPerThread>>>(p);
}
```

```cpp
#include <cuda_runtime.h>
#include <cuda_bf16.h>
#include <cuda.h>
#include <stdint.h>

namespace {

constexpr int NCTA  = 128;
constexpr int NW    = 8;
constexpr int NSLOT = 7;
constexpr int TILE  = 4096;
constexpr int NFIRST = 3;
constexpr int NRF = 4;

constexpr int OFF_BAR = NW * NSLOT * TILE;
constexpr int OFF_RED = OFF_BAR + 512;
constexpr int OFF_ST  = OFF_RED + 2048;
constexpr int OFF_ML  = OFF_ST + 64;
constexpr int OFF_META = OFF_ML + 256;
constexpr int SMEM_BYTES = OFF_META + 128;

constexpr uint64_t POL_EVICT_FIRST = 0x12F0000000000000ull;
constexpr int SPIN_LIMIT = 1 << 20;
constexpr unsigned FULL = 0xffffffffu;

enum { M_KA = 0, M_VA = 1, M_KB = 2, M_VB = 3, M_WQA = 4, M_WQB = 5, M_WOA = 6, M_WOB = 7 };

constexpr uint32_t STEP_LAST = 1u << 13, STEP_RF = 1u << 20;
constexpr int NSTEP = 120;
struct Xchg {
    float q[NCTA][32];
    float part[NCTA][NW][96];
    float x[2][NCTA][32];
};
struct __align__(64) Params {
    CUtensorMap maps[8];
    const __nv_bfloat16* x;
    __nv_bfloat16* out;
    Xchg* xc;
    int first[4], last[4];
    uint32_t steps[NSTEP];
};
__device__ __align__(128) Xchg g_xchg;
#define TSTAMP(i)

__device__ __forceinline__ int lane_id() { int l; asm volatile("mov.u32 %0, %%laneid;" : "=r"(l)); return l; }
__device__ __forceinline__ bool mbar_try(uint32_t bar, uint32_t parity) {
    uint32_t ok;
    asm volatile("{\n.reg .pred p;\nmbarrier.try_wait.parity.shared::cta.b64 p, [%1], %2;\nselp.u32 %0, 1, 0, p;\n}"
                 : "=r"(ok) : "r"(bar), "r"(parity) : "memory");
    return __all_sync(0xffffffffu, ok);
}
__device__ __forceinline__ void mbar_wait(uint32_t bar, uint32_t parity) {
    if (!mbar_try(bar, parity)) {
        int n = 0;
        while (!mbar_try(bar, parity) && ++n < (1 << 17)) {}
    }
}
__device__ __forceinline__ void ldsm4(uint32_t* r, uint32_t a) {
    asm volatile("ldmatrix.sync.aligned.m8n8.x4.shared.b16 {%0,%1,%2,%3}, [%4];"
                 : "=r"(r[0]), "=r"(r[1]), "=r"(r[2]), "=r"(r[3]) : "r"(a) : "memory");
}
__device__ __forceinline__ void ldsm4t(uint32_t* r, uint32_t a) {
    asm volatile("ldmatrix.sync.aligned.m8n8.x4.trans.shared.b16 {%0,%1,%2,%3}, [%4];"
                 : "=r"(r[0]), "=r"(r[1]), "=r"(r[2]), "=r"(r[3]) : "r"(a) : "memory");
}
__device__ __forceinline__ void mma16816(float* c, uint32_t a0, uint32_t a1, uint32_t a2, uint32_t a3, uint32_t b0, uint32_t b1) {
    asm volatile("mma.sync.aligned.m16n8k16.row.col.f32.bf16.bf16.f32 {%0,%1,%2,%3}, {%4,%5,%6,%7}, {%8,%9}, {%0,%1,%2,%3};"
                 : "+f"(c[0]), "+f"(c[1]), "+f"(c[2]), "+f"(c[3])
                 : "r"(a0), "r"(a1), "r"(a2), "r"(a3), "r"(b0), "r"(b1));
}
__device__ __forceinline__ void mma16816(float* c, const uint32_t* a, uint32_t b0, uint32_t b1) { mma16816(c, a[0], a[1], a[2], a[3], b0, b1); }
__device__ __forceinline__ uint32_t movm(uint32_t a) {
    uint32_t d;
    asm volatile("movmatrix.sync.aligned.m8n8.trans.b16 %0, %1;" : "=r"(d) : "r"(a));
    return d;
}
__device__ __forceinline__ uint32_t pack_bf16(float lo, float hi) {
    uint32_t d;
    asm("cvt.rn.bf16x2.f32 %0, %1, %2;" : "=r"(d) : "f"(hi), "f"(lo));
    return d;
}
__device__ __forceinline__ float bf_lo(uint32_t v) { return __uint_as_float(v << 16); }
__device__ __forceinline__ float bf_hi(uint32_t v) { return __uint_as_float(v & 0xffff0000u); }
__device__ __forceinline__ float ex2(float v) { float d; asm("ex2.approx.ftz.f32 %0, %1;" : "=f"(d) : "f"(v)); return d; }
__device__ __forceinline__ float rcp(float v) { float d; asm("rcp.approx.ftz.f32 %0, %1;" : "=f"(d) : "f"(v)); return d; }
__device__ __forceinline__ float rsq(float v) { float d; asm("rsqrt.approx.ftz.f32 %0, %1;" : "=f"(d) : "f"(v)); return d; }
__device__ __forceinline__ uint32_t tagged(float v, uint32_t tag) { return (__float_as_uint(v) & ~3u) | tag; }

__device__ __forceinline__ void st_rlx8(void* p, uint32_t a, uint32_t b) {
    asm volatile("{\n.reg .b64 l;\nmov.b64 l, {%1,%2};\nst.relaxed.gpu.global.b64 [%0], l;\n}" :: "l"(p), "r"(a), "r"(b) : "memory");
}
__device__ __forceinline__ void ld_rlx8(uint32_t& a, uint32_t& b, const void* p) {
    asm volatile("{\n.reg .b64 l;\nld.relaxed.gpu.global.b64 l, [%2];\nmov.b64 {%0,%1}, l;\n}" : "=r"(a), "=r"(b) : "l"(p) : "memory");
}
__device__ __forceinline__ void st_rlx16(void* p, uint32_t a, uint32_t b, uint32_t c, uint32_t d) {
    asm volatile("{\n.reg .b64 l, h;\n.reg .b128 v;\nmov.b64 l, {%1,%2};\nmov.b64 h, {%3,%4};\nmov.b128 v, {l,h};\n"
                 "st.relaxed.gpu.global.b128 [%0], v;\n}" :: "l"(p), "r"(a), "r"(b), "r"(c), "r"(d) : "memory");
}
__device__ __forceinline__ void ld_rlx16(uint32_t* r, const void* p) {
    asm volatile("{\n.reg .b64 l, h;\n.reg .b128 v;\nld.relaxed.gpu.global.b128 v, [%4];\nmov.b128 {l,h}, v;\n"
                 "mov.b64 {%0,%1}, l;\nmov.b64 {%2,%3}, h;\n}" : "=r"(r[0]), "=r"(r[1]), "=r"(r[2]), "=r"(r[3]) : "l"(p) : "memory");
}
__device__ __forceinline__ void sts(uint32_t a, float v) { asm volatile("st.shared.f32 [%0], %1;" :: "r"(a), "f"(v) : "memory"); }
__device__ __forceinline__ void sts2(uint32_t a, float x, float y) { asm volatile("st.shared.v2.f32 [%0], {%1,%2};" :: "r"(a), "f"(x), "f"(y) : "memory"); }
__device__ __forceinline__ void lds4(float* v, uint32_t a) { asm volatile("ld.shared.v4.f32 {%0,%1,%2,%3}, [%4];" : "=f"(v[0]), "=f"(v[1]), "=f"(v[2]), "=f"(v[3]) : "r"(a) : "memory"); }

constexpr float SCALE_LOG2E = 0.08838834764831845f * 1.4426950408889634f;
constexpr float MAX_SLACK = 8.f;

__device__ __forceinline__ uint32_t slot_addr(uint32_t wslots, uint32_t e) { return wslots + (e & 7u) * TILE; }
__device__ __forceinline__ uint32_t slot_bar(uint32_t wbars, uint32_t e) { return wbars + (e & 7u) * 8; }
__device__ __forceinline__ void wait_step(uint32_t wbars, uint32_t e) { mbar_wait(slot_bar(wbars, e), (e >> 3) & 1u); }
__device__ __forceinline__ void refill(const Params& p, uint32_t e, uint32_t wslots, uint32_t wbars, int w) {
    const unsigned char* m = reinterpret_cast<const unsigned char*>(&p.maps[0]) + ((e << 1) & 0x380u);
    const int c2 = w + ((e >> 6) & 0x78u), c3 = blockIdx.x & 15, c4 = blockIdx.x >> 4;
    asm volatile("{\n.reg .pred p, q;\n"
                 "elect.sync _|p, 0xffffffff;\n"
                 "setp.ne.and.u32 q, %9, 0, p;\n"
                 "setp.ne.and.u32 p, %8, 0, p;\n"
                 "@p mbarrier.arrive.expect_tx.shared::cta.b64 _, [%6], 4096;\n"
                 "@p cp.async.bulk.tensor.5d.shared::cluster.global.mbarrier::complete_tx::bytes.L2::cache_hint [%0], [%1, {%2,%2,%3,%4,%5}], [%6], %7;\n"
                 "@q cp.async.bulk.prefetch.tensor.5d.L2.global.tile [%1, {%2,%2,%3,%4,%5}];\n"
                 "}"
                 :: "r"(slot_addr(wslots, e >> 16)), "l"(m), "r"(0), "r"(c2), "r"(c3), "r"(c4), "r"(slot_bar(wbars, e >> 16)), "l"(POL_EVICT_FIRST),
                    "r"(e & 16u), "r"(e & 32u) : "memory");
}

__device__ __forceinline__ void refill_if(const Params& p, uint32_t e, uint32_t wslots, uint32_t wbars, int w) {
    if (e & 48u) refill(p, e, wslots, wbars, w);
}
template <class T> __device__ __forceinline__ T* pin(T* q) { asm volatile("" : "+l"(q)); return q; }
__device__ __forceinline__ uint32_t pin(uint32_t v) { asm volatile("" : "+r"(v)); return v; }
__device__ __forceinline__ float selp(float a, float b, bool c) {
    float d;
    asm("{\n.reg .pred p;\nsetp.ne.u32 p, %3, 0;\nselp.f32 %0, %1, %2, p;\n}" : "=f"(d) : "f"(a), "f"(b), "r"((uint32_t)c));
    return d;
}

constexpr uint32_t SWAP = 0x90;
struct Attn {
    uint32_t qf[8];
    float o[16];
    float n0, n1;
    float l0, l1;
    uint32_t mv;
};
__device__ __forceinline__ void load_k(uint32_t* f, uint32_t base) {
#pragma unroll
    for (int j = 0; j < 4; j++) {
        ldsm4(f + 8 * j, base ^ (j << 5));
        ldsm4(f + 8 * j + 4, (base ^ (j << 5) ^ SWAP) + 2048);
    }
}
__device__ __forceinline__ void load_v(uint32_t* f, uint32_t base) {
#pragma unroll
    for (int j = 0; j < 4; j++) ldsm4t(f + 8 * j, base ^ (j << 5));
#pragma unroll
    for (int j = 0; j < 4; j++) ldsm4t(f + 8 * j + 4, (base ^ (j << 5) ^ SWAP) + 2048);
}
__device__ __forceinline__ void qk(const Attn& a, const uint32_t* f, float* s) {
    float c[8];
#pragma unroll
    for (int i = 0; i < 8; i++) c[i] = 0.f;
#pragma unroll
    for (int j = 0; j < 4; j++) {
        mma16816(c, f + 8 * j, a.qf[2 * j], a.qf[2 * j + 1]);
        mma16816(c + 4, f + 8 * j + 4, a.qf[2 * j], a.qf[2 * j + 1]);
    }
#pragma unroll
    for (int i = 0; i < 4; i++) s[i] = __uint_as_float((__float_as_uint(c[i]) & a.mv) | (__float_as_uint(c[i + 4]) & ~a.mv));
}
__device__ __forceinline__ void pv(Attn& a, const uint32_t* f, const uint32_t* b) {
#pragma unroll
    for (int j = 0; j < 4; j++) mma16816(a.o + 4 * j, f + 8 * j, b[0], b[1]);
#pragma unroll
    for (int j = 0; j < 4; j++) mma16816(a.o + 4 * j, f + 8 * j + 4, b[2], b[3]);
}
__device__ __forceinline__ void probs(Attn& a, float* y, uint32_t* b) {
#pragma unroll
    for (int i = 0; i < 4; i++) y[i] = ex2(y[i]);
    const uint32_t p0 = pack_bf16(y[0], y[1]), p1 = pack_bf16(y[2], y[3]);
    b[0] = movm(p0 & a.mv); b[1] = movm(p1 & a.mv);
    b[2] = movm(p0 & ~a.mv); b[3] = movm(p1 & ~a.mv);
    a.l0 += y[0] + y[2];
    a.l1 += y[1] + y[3];
    asm volatile("" : "+f"(a.l0), "+f"(a.l1));
}
__device__ __forceinline__ void softmax_step(Attn& a, float* s, uint32_t* b) {
    float y[4];
#pragma unroll
    for (int i = 0; i < 4; i++) s[i] += __shfl_xor_sync(FULL, s[i], 6);
#pragma unroll
    for (int i = 0; i < 4; i++) y[i] = fmaf(s[i], SCALE_LOG2E, (i & 1) ? a.n1 : a.n0);
    if (__any_sync(FULL, fmaxf(fmaxf(y[0], y[1]), fmaxf(y[2], y[3])) > MAX_SLACK)) {
        float t0 = fmaxf(s[0], s[2]), t1 = fmaxf(s[1], s[3]);
#pragma unroll
        for (int d = 4; d <= 16; d <<= 1) {
            t0 = fmaxf(t0, __shfl_xor_sync(FULL, t0, d));
            t1 = fmaxf(t1, __shfl_xor_sync(FULL, t1, d));
        }
        t0 = fminf(-SCALE_LOG2E * t0, a.n0); t1 = fminf(-SCALE_LOG2E * t1, a.n1);
        const float r0 = ex2(t0 - a.n0), r1 = ex2(t1 - a.n1);
        a.n0 = t0; a.n1 = t1;
        a.l0 *= r0; a.l1 *= r1;
#pragma unroll
        for (int i = 0; i < 16; i += 2) { a.o[i] *= r0; a.o[i + 1] *= r1; }
#pragma unroll
        for (int i = 0; i < 4; i++) y[i] = fmaf(s[i], SCALE_LOG2E, (i & 1) ? a.n1 : a.n0);
    }
    probs(a, y, b);
}

constexpr uint32_t NOPATCH = 0xffffffffu, B87 = 0x87878787u;
__device__ __forceinline__ void lds4u(uint32_t* v, uint32_t a) { asm volatile("ld.shared.v4.u32 {%0,%1,%2,%3}, [%4];" : "=r"(v[0]), "=r"(v[1]), "=r"(v[2]), "=r"(v[3]) : "r"(a) : "memory"); }
__device__ __forceinline__ void sts4u(uint32_t a, const uint32_t* v) { asm volatile("st.shared.v4.u32 [%0], {%1,%2,%3,%4};" :: "r"(a), "r"(v[0]), "r"(v[1]), "r"(v[2]), "r"(v[3]) : "memory"); }
__device__ __forceinline__ void sts_u8(uint32_t a, uint32_t v) { asm volatile("st.shared.u8 [%0], %1;" :: "r"(a), "r"(v) : "memory"); }
__device__ __forceinline__ void sts_u16(uint32_t a, uint32_t v) { asm volatile("st.shared.u16 [%0], %1;" :: "r"(a), "r"(v) : "memory"); }
__device__ __forceinline__ uint32_t lds_u16(uint32_t a) { uint32_t v; asm volatile("ld.shared.u16 %0, [%1];" : "=r"(v) : "r"(a) : "memory"); return v; }
__device__ __forceinline__ uint32_t lds_u32(uint32_t a) { uint32_t v; asm volatile("ld.shared.u32 %0, [%1];" : "=r"(v) : "r"(a) : "memory"); return v; }
__device__ __forceinline__ uint32_t bitsel(uint32_t a, uint32_t b, uint32_t m) {
    uint32_t d;
    asm("lop3.b32 %0, %1, %2, %3, 0xE4;" : "=r"(d) : "r"(a), "r"(b), "r"(m));
    return d;
}
__device__ __forceinline__ uint32_t mul2(uint32_t a, uint32_t b) { uint32_t d; asm("mul.rn.bf16x2 %0, %1, %2;" : "=r"(d) : "r"(a), "r"(b)); return d; }

__device__ __forceinline__ void pack_tile(uint32_t src, uint32_t dst, uint32_t meta, uint32_t id, uint32_t& patch, int lane) {
    src += lane * 16; dst += lane * 16;
    uint32_t m0 = 0, m1 = 0;
#pragma unroll
    for (int k = 0; k < 8; k++) {
        uint32_t r[4];
        lds4u(r, src + k * 512);
        asm("max.xorsign.abs.bf16x2 %0, %0, %1;" : "+r"(m0) : "r"(r[0]));
        asm("max.xorsign.abs.bf16x2 %0, %0, %1;" : "+r"(m1) : "r"(r[1]));
        asm("max.xorsign.abs.bf16x2 %0, %0, %1;" : "+r"(m0) : "r"(r[2]));
        asm("max.xorsign.abs.bf16x2 %0, %0, %1;" : "+r"(m1) : "r"(r[3]));
    }
    asm("max.xorsign.abs.bf16x2 %0, %0, %1;" : "+r"(m0) : "r"(m1));
    const int top = __reduce_max_sync(FULL, (int)max((m0 >> 23) & 0xffu, (m0 >> 7) & 0xffu));
    uint32_t sh = min(max(top - 15, 0), 126);
    const uint32_t up = (127u + sh) * 0x00800080u, down = (127u - sh) * 0x00800080u;
#pragma unroll 1
    for (int hf = 0; hf < 2; hf++) {
        uint32_t o[12], bad = 0;
#pragma unroll
        for (int k = 0; k < 4; k++) {
            uint32_t r[4], s[4];
            lds4u(r, src + hf * 2048 + k * 512);
#pragma unroll
            for (int i = 0; i < 4; i++) s[i] = mul2(r[i], down);
            o[3 * k] = __byte_perm(s[0], s[1], 0x6420);
            o[3 * k + 1] = __byte_perm(s[2], s[3], 0x6420);
            const uint32_t h0 = __byte_perm(s[0], s[1], 0x7531), h1 = __byte_perm(s[2], s[3], 0x7531);
            o[3 * k + 2] = bitsel(h1, __funnelshift_l(h0, h0, 4), B87);
            uint32_t d = (h0 | h1) & ~B87;
#pragma unroll
            for (int i = 0; i < 4; i++) d |= mul2(s[i], up) ^ r[i];
            if (d) bad |= 15u << (4 * k);
        }
        bad = __reduce_or_sync(FULL, bad);
#pragma unroll 1
        for (; bad != 0u && sh != 0xffu; bad &= bad - 1u) {
            const int k = __ffs(bad) - 1;
            const uint32_t at = hf * 2048 + (k >> 2) * 512 + (k & 3) * 4;
            const uint32_t r = lds_u32(src + at);
            uint32_t b = mul2(mul2(r, down) & 0x87ff87ffu, up) ^ r;
#pragma unroll 1
            for (uint32_t lanes; (lanes = __ballot_sync(FULL, b != 0u)) != 0u;) {
                const int n = __popc(__ballot_sync(FULL, patch != NOPATCH));
                if (n == 32) {
                    sh = 0xffu;
                    if ((patch >> 28) == id) patch = NOPATCH;
                    break;
                }
                const uint32_t hi = (b & 0xffffu) ? 0u : 16u;
                const int from = __ffs(lanes) - 1;
                const uint32_t ent = __shfl_sync(FULL, (id << 28) | ((at + lane * 16 + (hi >> 3)) << 16) | ((r >> hi) & 0xffffu), from);
                if (lane == n) patch = ent;
                if (lane == from) b &= ~(0xffffu << hi);
            }
        }
#pragma unroll
        for (int j = 0; j < 3; j++) sts4u(dst + hf * 1536 + j * 512, o + 4 * j);
    }
    if (lane == 0) sts_u8(meta, sh);
}
__device__ __forceinline__ void unpack_tile(const uint32_t* o, uint32_t dst, uint32_t up) {
#pragma unroll
    for (int k = 0; k < 8; k++) {
        const uint32_t n = o[3 * k + 2];
        const uint32_t h0 = __funnelshift_r(n, n, 4) & B87, h1 = n & B87;
        uint32_t r[4];
        r[0] = mul2(__byte_perm(o[3 * k], h0, 0x5140), up); r[1] = mul2(__byte_perm(o[3 * k], h0, 0x7362), up);
        r[2] = mul2(__byte_perm(o[3 * k + 1], h1, 0x5140), up); r[3] = mul2(__byte_perm(o[3 * k + 1], h1, 0x7362), up);
        sts4u(dst + k * 512, r);
    }
}

__device__ __forceinline__ uint32_t add_residual(uint32_t xp, const uint32_t (*v)[4], bool half) {
    float r[4];
#pragma unroll
    for (int k = 0; k < 4; k++)
        r[k] = (__uint_as_float(v[0][k]) + __uint_as_float(v[1][k])) + (__uint_as_float(v[2][k]) + __uint_as_float(v[3][k]));
    const float y0 = selp(r[2], r[0], half) + __shfl_xor_sync(FULL, selp(r[0], r[2], half), 16);
    const float y1 = selp(r[3], r[1], half) + __shfl_xor_sync(FULL, selp(r[1], r[3], half), 16);
    const uint32_t yb = pack_bf16(y0, y1);
    return pack_bf16(bf_lo(xp) + bf_lo(yb), bf_hi(xp) + bf_hi(yb));
}

__device__ __forceinline__ void gemv_load(uint32_t (*f)[4], uint32_t tile, int lane) {
    const int mi = lane >> 3, r = lane & 7;
    const uint32_t a0 = tile + ((mi >> 1) * 8 + r) * 64 + (((mi & 1) ^ (r >> 1)) << 4);
#pragma unroll
    for (int j = 0; j < 4; j++) {
        ldsm4t(f[2 * j], a0 + j * 1024);
        ldsm4t(f[2 * j + 1], (a0 ^ 32u) + j * 1024);
    }
}
template <bool STATS>
__device__ __forceinline__ void gemv_mma(const uint32_t (*f)[4], uint32_t vpair, float& y0, float& y1, float* st, int lane) {
    const int src = ((lane >> 1) & 1) + 16 * (lane & 1);
    float c[4][4];
    uint32_t x[8];
#pragma unroll
    for (int j = 0; j < 8; j++) x[j] = __shfl_sync(FULL, vpair, 2 * j + src);
#pragma unroll
    for (int i = 0; i < 4; i++) { c[0][i] = c[1][i] = c[2][i] = c[3][i] = 0.f; if (STATS) st[i] = 0.f; }
#pragma unroll
    for (int j = 0; j < 4; j++) {
        uint32_t b0 = x[2 * j], b1 = x[2 * j + 1];
        if (STATS && (lane & 4)) b0 = b1 = 0x3f803f80u;
        mma16816(c[2 * (j & 1)], f[2 * j], b0, b1);
        mma16816(c[2 * (j & 1) + 1], f[2 * j + 1], b0, b1);
        if (STATS) mma16816(st, x[2 * j], x[2 * j], x[2 * j + 1], x[2 * j + 1], b0, b1);
    }
    const bool t1 = lane & 1, t2 = lane & 2;
    y0 = selp(selp(c[1][2] + c[3][2], c[1][0] + c[3][0], t1), selp(c[0][2] + c[2][2], c[0][0] + c[2][0], t1), t2);
    if (STATS) y1 = selp(selp(c[1][3] + c[3][3], c[1][1] + c[3][1], t1), selp(c[0][3] + c[2][3], c[0][1] + c[2][1], t1), t2);
}

__global__ void __launch_bounds__(NW * 32, 1)
decode_kernel(const __grid_constant__ Params p) {
    extern __shared__ __align__(1024) unsigned char smem_raw[];
    const uint32_t smem = (uint32_t)__cvta_generic_to_shared(smem_raw);
    int lane = lane_id();
    const int w = __shfl_sync(FULL, threadIdx.x >> 5, 0);
    const int cta = blockIdx.x, h = cta >> 4;
    const uint32_t wslots = smem + w * (NSLOT * TILE);
    const uint32_t wbars = smem + OFF_BAR + w * (NSLOT * 8);
    TSTAMP(0);
    if (lane < NSLOT) {
        asm volatile("mbarrier.init.shared::cta.b64 [%0], 1;" :: "r"(wbars + lane * 8) : "memory");
        asm volatile("fence.proxy.async.shared::cta;" ::: "memory");
    }
    __syncwarp();
    refill(p, 16 | (M_WQA << 6), wslots, wbars, w);
#pragma unroll
    for (int i = 1; i < NFIRST; i++) refill(p, (i << 16) | 16 | (((i - 1) & 1) << 6) | (((i - 1) >> 1) << 9), wslots, wbars, w);
    uint32_t xp = reinterpret_cast<const uint32_t*>(p.x)[32 * w + 2 * (lane & 15) + (lane >> 4)];
    TSTAMP(1);

    uint32_t rf[2 * NRF][24];
    uint32_t patch = NOPATCH;
#pragma unroll
    for (int i = 0; i < 2 * NRF; i++)
#pragma unroll
        for (int j = 0; j < 24; j++) rf[i][j] = 0u;

#pragma unroll 1
    for (int layer = 0; layer < 4; layer++) {
        const uint32_t tag = (layer + 1) & 3;
        int c = p.first[layer];
        Attn a;
        {
            const uint32_t e = p.steps[c];
            const int half = lane >> 4;
            const uint32_t ptag = layer & 3;
            const float* src = pin(&p.xc->x[(layer + 1) & 1][16 * half + 2 * w][4 * (lane & 15)]);
            uint32_t v[4][4], f[8][4];
            if (layer > 0) {
#pragma unroll
                for (int j = 0; j < 4; j++) ld_rlx16(v[j], src + j * 1024);
            } else {
#pragma unroll
                for (int j = 0; j < 4; j++) v[j][0] = v[j][1] = v[j][2] = v[j][3] = 0u;
            }
            wait_step(wbars, e);
            gemv_load(f, slot_addr(wslots, e), lane);
            asm volatile("" :: "r"(f[7][3]), "r"(f[6][3]) : "memory");
            refill_if(p, e, wslots, wbars, w);
            if (layer > 0) {
                int it = 0;
                while (!__all_sync(FULL, (((v[0][0] ^ ptag) | (v[1][0] ^ ptag) | (v[2][0] ^ ptag) | (v[3][0] ^ ptag)) & 3u) == 0u) && ++it < SPIN_LIMIT) {
#pragma unroll
                    for (int j = 0; j < 4; j++)
                        if ((v[j][0] ^ ptag) & 3u) ld_rlx16(v[j], src + j * 1024);
                }
                xp = add_residual(xp, v, half);
                TSTAMP(layer * 8);
            }
            refill_if(p, p.steps[c + 1], wslots, wbars, w);
            float y0, y1, st[4];
            gemv_mma<true>(f, xp, y0, y1, st, lane);
            float* dst = pin(&p.xc->q[cta][2 * lane]);
            sts2(smem + OFF_RED + w * 256 + (8 * (lane & 3) + (lane >> 2)) * 8, y0, y1);
            if (lane == 0) sts2(smem + OFF_ST + w * 8, st[0], st[1]);
            __syncthreads();
            if (w == 0) {
                float u[8][4], z[16];
#pragma unroll
                for (int i = 0; i < 4; i++) lds4(z + 4 * i, smem + OFF_ST + 16 * i);
#pragma unroll
                for (int i = 0; i < 8; i++) lds4(u[i], smem + OFF_RED + i * 256 + (lane & 15) * 16);
                const float sq = ((z[0] + z[2]) + (z[4] + z[6])) + ((z[8] + z[10]) + (z[12] + z[14]));
                const float su = ((z[1] + z[3]) + (z[5] + z[7])) + ((z[9] + z[11]) + (z[13] + z[15]));
                const float mean = su * (1.f / 512.f);
                const float rstd = rsq(fmaxf(fmaf(-mean, mean, sq * (1.f / 512.f)), 0.f) + 1e-5f);
                float r[4];
#pragma unroll
                for (int k = 0; k < 4; k++) r[k] = ((u[0][k] + u[1][k]) + (u[2][k] + u[3][k])) + ((u[4][k] + u[5][k]) + (u[6][k] + u[7][k]));
                if (lane < 16) st_rlx8(dst, tagged(fmaf(-mean, r[1], r[0]) * rstd, tag), __float_as_uint(fmaf(-mean, r[3], r[2]) * rstd));
            }
            TSTAMP(2 + layer * 8);
            refill_if(p, p.steps[c + 2], wslots, wbars, w);
            refill_if(p, p.steps[c + 3], wslots, wbars, w);
            c += 4;
            __syncthreads();
        }
        const uint32_t offk = (((lane >> 3) & 1) * 8 + (lane & 7)) * 128 + ((((lane >> 4) & 1) ^ (lane & 7)) << 4);
        const uint32_t offv = (((lane >> 4) & 1) * 8 + (lane & 7)) * 128 + ((((lane >> 3) & 1) ^ (lane & 7)) << 4);
        a.mv = pin((((lane >> 2) ^ (lane >> 1)) & 1) - 1u);
        uint32_t f[32];
        if (layer & 1) {
            const uint32_t e = p.steps[c];
            wait_step(wbars, e);
            load_k(f, slot_addr(wslots, e) + offk);
            asm volatile("" :: "r"(f[31]), "r"(f[27]) : "memory");
            refill_if(p, e, wslots, wbars, w);
        } else {
#pragma unroll
            for (int i = 0; i < 32; i++) f[i] = 0u;
        }
        {
            const float* qsrc = pin(&p.xc->q[h * 16 + 2 * w][2 * lane]);
            const uint32_t qd = pin(smem + OFF_RED + ((lane >> 4) * 32 + 4 * ((w >> 1) + 4 * (w & 1)) + (lane & 3)) * 16 + (lane & 12));
            uint32_t v0, v1;
            int it = 0;
            do { ld_rlx8(v0, v1, qsrc); } while (!__all_sync(FULL, ((v0 ^ tag) & 3u) == 0u) && ++it < SPIN_LIMIT);
            sts(qd, __uint_as_float(pack_bf16(__uint_as_float(v0), __uint_as_float(v1))));
            __syncthreads();
            lds4(reinterpret_cast<float*>(a.qf), smem + OFF_RED + lane * 16);
            lds4(reinterpret_cast<float*>(a.qf + 4), smem + OFF_RED + 512 + lane * 16);
        }
        TSTAMP(3 + layer * 8);
        if (layer & 1) {
            const uint32_t ek1 = p.steps[c + 1], ev0 = p.steps[c + 2], ev = p.steps[c + 3];
            uint32_t b[8];
            float s[8];
            qk(a, f, s);
            wait_step(wbars, ek1);
            load_k(f, slot_addr(wslots, ek1) + offk);
            qk(a, f, s + 4);
            refill(p, ek1, wslots, wbars, w);
#pragma unroll
            for (int i = 0; i < 8; i++) s[i] += __shfl_xor_sync(FULL, s[i], 6);
            float t0 = fmaxf(fmaxf(s[0], s[2]), fmaxf(s[4], s[6])), t1 = fmaxf(fmaxf(s[1], s[3]), fmaxf(s[5], s[7]));
#pragma unroll
            for (int d = 4; d <= 16; d <<= 1) {
                t0 = fmaxf(t0, __shfl_xor_sync(FULL, t0, d));
                t1 = fmaxf(t1, __shfl_xor_sync(FULL, t1, d));
            }
            a.n0 = -SCALE_LOG2E * t0; a.n1 = -SCALE_LOG2E * t1;
            a.l0 = a.l1 = 0.f;
#pragma unroll
            for (int i = 0; i < 8; i++) s[i] = fmaf(s[i], SCALE_LOG2E, (i & 1) ? a.n1 : a.n0);
            wait_step(wbars, ev0);
            load_v(f, slot_addr(wslots, ev0) + offv);
            probs(a, s, b);
            probs(a, s + 4, b + 4);
#pragma unroll
            for (int i = 0; i < 16; i++) a.o[i] = 0.f;
            pv(a, f, b);
            refill(p, ev0, wslots, wbars, w);
            wait_step(wbars, ev);
            load_v(f, slot_addr(wslots, ev) + offv);
            pv(a, f, b + 4);
        } else {
#pragma unroll
            for (int i = 0; i < 16; i++) a.o[i] = 0.f;
            a.n0 = a.n1 = INFINITY;
            a.l0 = a.l1 = 0.f;
#pragma unroll 1
            for (;;) {
                float s[4];
                uint32_t b[4];
                const uint32_t ek = p.steps[c++];
                const uint32_t ev = p.steps[c++];
                if ((ek & STEP_RF) && layer == 2) {
                    const uint32_t r = (ek >> 21) & 3u;
                    const uint32_t bb = lds_u16(smem + OFF_META + w * 16 + 2 * r), l16 = lane_id() * 16;
                    const uint32_t ak = slot_addr(wslots, ek), av = slot_addr(wslots, ev);
                    const uint32_t bk = (127u + (bb & 0xffu)) * 0x00800080u, bv = (127u + (bb >> 8)) * 0x00800080u;
#pragma unroll
                    for (int i = 0; i < NRF; i++) if (r == i) {
                        unpack_tile(rf[2 * i], ak + l16, bk);
                        unpack_tile(rf[2 * i + 1], av + l16, bv);
                    }
                    __syncwarp();
                    if ((patch >> 29) == r) sts_u16(((patch >> 28) & 1u ? av : ak) + ((patch >> 16) & 0xfffu), patch);
                    asm volatile("fence.proxy.async.shared::cta;" ::: "memory");
                    const uint32_t again = __ballot_sync(FULL, ((bb >> (l16 >> 1)) & 0xffu) == 0xffu) & 3u;
                    asm volatile("{\n.reg .pred p, q;\nelect.sync _|p, 0xffffffff;\n"
                                 "setp.eq.and.u32 q, %2, 0, p;\n@q mbarrier.arrive.shared::cta.b64 _, [%0];\n"
                                 "setp.eq.and.u32 q, %3, 0, p;\n@q mbarrier.arrive.shared::cta.b64 _, [%1];\n}"
                                 :: "r"(slot_bar(wbars, ek)), "r"(slot_bar(wbars, ev)), "r"(again & 1u), "r"(again & 2u) : "memory");
                    if (again) {
                        refill(p, ((again & 1u) << 4) | (r << 9) | ((ek & 7u) << 16), wslots, wbars, w);
                        refill(p, ((again & 2u) << 3) | (1 << 6) | (r << 9) | ((ev & 7u) << 16), wslots, wbars, w);
                    }
                }
                wait_step(wbars, ek);
                load_k(f, slot_addr(wslots, ek) + offk);
                qk(a, f, s);
                refill(p, ek, wslots, wbars, w);
                softmax_step(a, s, b);
                wait_step(wbars, ev);
                load_v(f, slot_addr(wslots, ev) + offv);
                pv(a, f, b);
                refill(p, ev, wslots, wbars, w);
                if ((ek & STEP_RF) && layer == 0) {
                    const uint32_t r = (ek >> 21) & 3u;
                    const int ln = lane_id();
                    __syncwarp();
#pragma unroll 1
                    for (int i = 0; i < 2; i++) {
                        const uint32_t at = slot_addr(wslots, i ? ev : ek);
                        pack_tile(at, at, smem + OFF_META + w * 16 + 2 * r + i, 2 * r + i, patch, ln);
                    }
                    const uint32_t l16 = ln * 16;
                    const uint32_t ak = slot_addr(wslots, ek) + l16, av = slot_addr(wslots, ev) + l16;
#pragma unroll
                    for (int i = 0; i < NRF; i++) if (r == i) {
#pragma unroll
                        for (int j = 0; j < 6; j++) { lds4u(&rf[2 * i][4 * j], ak + j * 512); lds4u(&rf[2 * i + 1][4 * j], av + j * 512); }
                    }
                    asm volatile("fence.proxy.async.shared::cta;" ::: "memory");
                    __syncwarp();
                }
                if (ev & STEP_LAST) break;
            }
        }
        c = p.last[layer] + 1;
        const uint32_t ev = p.steps[c++];
        lane = lane_id();
        const int g = lane >> 2, t = lane & 3, half = lane >> 4, c16 = lane & 15;
        TSTAMP(4 + layer * 8);
        uint32_t v[8][4], mj, lj;
        const float* src = pin(&p.xc->part[h * 16 + half][w][4 * c16]);
        const float* ssrc = pin(&p.xc->part[h * 16 + c16][w][64]);
        {
            a.l0 += __shfl_xor_sync(FULL, a.l0, 4);
            a.l1 += __shfl_xor_sync(FULL, a.l1, 4);
            a.l0 += __shfl_xor_sync(FULL, a.l0, 8);
            a.l1 += __shfl_xor_sync(FULL, a.l1, 8);
            const uint32_t o0 = slot_addr(wslots, ev) + ((4 * (t & 1) + (t >> 1)) * 96 + 8 * t + g) * 4;
#pragma unroll
            for (int i = 0; i < 4; i++) {
                sts(o0 + i * 64, a.o[4 * i]);
                sts(o0 + i * 64 + 192 * 4, a.o[4 * i + 1]);
                sts(o0 + i * 64 + 32, a.o[4 * i + 2]);
                sts(o0 + i * 64 + 192 * 4 + 32, a.o[4 * i + 3]);
            }
            a.l0 += __shfl_xor_sync(FULL, a.l0, 16);
            a.l1 += __shfl_xor_sync(FULL, a.l1, 16);
            if (lane < 2) {
                const uint32_t ml = smem + OFF_ML + lane * 128 + w * 4;
                sts(ml, -a.n0); sts(ml + 64, -a.n1); sts(ml + 32, a.l0); sts(ml + 96, a.l1);
            }
            float* dst = pin(&p.xc->part[cta][w][4 * lane]);
            const uint32_t mlr = pin(smem + OFF_ML + (w >> 1) * 64 + half * 16);
            const uint32_t ro = pin(slot_addr(smem, ev) + half * (4 * NSLOT * TILE) + (w * 96 + 8 * ((w >> 2) + 2 * (w & 1)) + 4 * c16) * 4);
            __syncthreads();
            float m[8], l[4], u[4][4];
            lds4(m, mlr);
            lds4(m + 4, mlr ^ 16u);
#pragma unroll
            for (int i = 0; i < 4; i++) lds4(u[i], ro + i * (NSLOT * TILE));
            lds4(l, mlr + 32);
            const float M = fmaxf(fmaxf(fmaxf(m[0], m[1]), fmaxf(m[2], m[3])), fmaxf(fmaxf(m[4], m[5]), fmaxf(m[6], m[7])));
            float z[4], r[4];
#pragma unroll
            for (int i = 0; i < 4; i++) z[i] = ex2(m[i] - M);
#pragma unroll
            for (int k = 0; k < 4; k++) r[k] = fmaf(z[0], u[0][k], z[1] * u[1][k]) + fmaf(z[2], u[2][k], z[3] * u[3][k]);
            float L = fmaf(z[0], l[0], z[1] * l[1]) + fmaf(z[2], l[2], z[3] * l[3]);
#pragma unroll
            for (int k = 0; k < 4; k++) r[k] += __shfl_xor_sync(FULL, r[k], 16);
            L += __shfl_xor_sync(FULL, L, 16);
            if (lane <= 16) st_rlx16(dst, tagged(selp(M, r[0], half), tag), __float_as_uint(selp(L, r[1], half)), __float_as_uint(r[2]), __float_as_uint(r[3]));
            TSTAMP(5 + layer * 8);
            ld_rlx8(mj, lj, ssrc);
#pragma unroll
            for (int j = 0; j < 8; j++) ld_rlx16(v[j], src + j * (2 * NW * 96));
            asm volatile("fence.proxy.async.shared::cta;" ::: "memory");
            __syncthreads();
            refill_if(p, ev, wslots, wbars, w);
            refill_if(p, p.steps[c], wslots, wbars, w);
        }
        {
            const uint32_t e = p.steps[c + 1];
            int it = 0;
            for (;;) {
                uint32_t bad = mj ^ tag;
#pragma unroll
                for (int j = 0; j < 8; j++) bad |= v[j][0] ^ tag;
                if (__all_sync(FULL, (bad & 3u) == 0u) || ++it >= SPIN_LIMIT) break;
                if ((mj ^ tag) & 3u) ld_rlx8(mj, lj, ssrc);
#pragma unroll
                for (int j = 0; j < 8; j++)
                    if ((v[j][0] ^ tag) & 3u) ld_rlx16(v[j], src + j * (2 * NW * 96));
            }
            TSTAMP(6 + layer * 8);
            const int key = (int)mj ^ (((int)mj >> 31) & 0x7fffffff);
            const int kmax = __reduce_max_sync(FULL, key);
            const float M = __int_as_float(kmax ^ ((kmax >> 31) & 0x7fffffff));
            const float fo = ex2(__uint_as_float(mj) - M);
            float fj[8], r[4];
#pragma unroll
            for (int j = 0; j < 8; j++) fj[j] = __shfl_sync(FULL, fo, 2 * j + half);
#pragma unroll
            for (int k = 0; k < 4; k++) {
                float r0 = fj[0] * __uint_as_float(v[0][k]), r1 = fj[1] * __uint_as_float(v[1][k]);
#pragma unroll
                for (int j = 2; j < 8; j += 2) { r0 = fmaf(fj[j], __uint_as_float(v[j][k]), r0); r1 = fmaf(fj[j + 1], __uint_as_float(v[j + 1][k]), r1); }
                r[k] = r0 + r1;
            }
            const float y0 = selp(r[2], r[0], half) + __shfl_xor_sync(FULL, selp(r[0], r[2], half), 16);
            const float y1 = selp(r[3], r[1], half) + __shfl_xor_sync(FULL, selp(r[1], r[3], half), 16);
            refill_if(p, p.steps[c + 2], wslots, wbars, w);
            wait_step(wbars, e);
            uint32_t fw[8][4];
            gemv_load(fw, slot_addr(wslots, e), lane);
            float L = fo * __uint_as_float(lj);
#pragma unroll
            for (int d = 1; d < 16; d <<= 1) L += __shfl_xor_sync(FULL, L, d);
            float y, unused;
            gemv_mma<false>(fw, pack_bf16(y0, y1), y, unused, nullptr, lane);
            float* dst = pin(&p.xc->x[layer & 1][cta][4 * lane]);
            sts(smem + OFF_RED + w * 128 + (8 * t + g) * 4, y * rcp(L));
            __syncthreads();
            if (w == 0) {
                float u[8][4];
#pragma unroll
                for (int i = 0; i < 8; i++) lds4(u[i], smem + OFF_RED + i * 128 + (lane & 7) * 16);
#pragma unroll
                for (int k = 0; k < 4; k++) r[k] = ((u[0][k] + u[1][k]) + (u[2][k] + u[3][k])) + ((u[4][k] + u[5][k]) + (u[6][k] + u[7][k]));
                if (lane < 8) st_rlx16(dst, tagged(r[0], tag), __float_as_uint(r[1]), __float_as_uint(r[2]), __float_as_uint(r[3]));
            }
            TSTAMP(7 + layer * 8);
            refill_if(p, e, wslots, wbars, w);
            refill_if(p, p.steps[c + 3], wslots, wbars, w);
            __syncthreads();
        }
    }
    if (cta == 0) {
        const float* src = &p.xc->x[1][16 * (lane >> 4) + 2 * w][4 * (lane & 15)];
        uint32_t v[4][4];
        int it = 0;
        do {
#pragma unroll
            for (int j = 0; j < 4; j++) ld_rlx16(v[j], src + j * 1024);
        } while (!__all_sync(FULL, ((v[0][0] | v[1][0] | v[2][0] | v[3][0]) & 3u) == 0u) && ++it < SPIN_LIMIT);
        reinterpret_cast<uint32_t*>(p.out)[32 * w + 2 * (lane & 15) + (lane >> 4)] = add_residual(xp, v, lane >> 4);
        TSTAMP(32);
    }
}

typedef CUresult (*EncodeFn)(CUtensorMap*, CUtensorMapDataType, cuuint32_t, void*, const cuuint64_t*, const cuuint64_t*,
                             const cuuint32_t*, const cuuint32_t*, CUtensorMapInterleave, CUtensorMapSwizzle,
                             CUtensorMapL2promotion, CUtensorMapFloatOOBfill);

void encode5d(EncodeFn enc, CUtensorMap* m, const void* ptr, uint32_t cols, uint32_t rows, uint32_t nchunk,
              uint64_t srow, uint64_t schunk, uint64_t ss, uint64_t sh, CUtensorMapSwizzle sw, CUtensorMapL2promotion promo) {
    cuuint64_t dims[5] = {cols, rows, nchunk, 16, 8};
    cuuint64_t strides[4] = {srow, schunk, ss, sh};
    cuuint32_t box[5] = {cols, rows, 1, 1, 1};
    cuuint32_t es[5] = {1, 1, 1, 1, 1};
    CUresult r = enc(m, CU_TENSOR_MAP_DATA_TYPE_BFLOAT16, 5, const_cast<void*>(ptr), dims, strides, box, es,
        CU_TENSOR_MAP_INTERLEAVE_NONE, sw, promo, CU_TENSOR_MAP_FLOAT_OOB_FILL_NONE);
    (void)r;
}

struct Sched {
    unsigned long long ord1 = 0x07251893ab4cdef6;
    unsigned long long ord3 = 0x469c1573e2ad08bf;
    unsigned long long l2 = 0xfffd4000;
    int parkat = 14;
    int nearly = 2;
    int promoB = 0;
    int promoW = 0;
    int d0 = 4;
    int dr = 3;
    int d1 = 2;
    int d3 = 5;
    int ch1 = 111111111, ch2 = 111101100, ch3 = 333244353;
    int pf1 = 100000000, pf2 = 100000000;
};

void build_schedule(Params& p, const Sched& sc) {
    struct Item { int map, tile, promote, park; };
    Item items[96];
    int n = 0;
    auto add = [&](int map, int tile, int promote, int park = 0) { items[n] = Item{map, tile, promote, park}; return n++; };
    auto dig = [](int v, int i) { for (int k = 8; k > i; k--) v /= 10; return v % 10; };
    int c1[32], n1 = 0, c3[32], n3 = 0;
    const int lp = NRF + 2, nearly = 2 * sc.nearly;
    const bool late = true;
    const int wq1 = add(M_WQA, 0, 0);
    int vlate = -1;
    for (int sp = 0; sp < 16; sp++) {
        const int pr = (sc.ord1 >> (60 - 4 * sp)) & 15;
        if (sp == sc.parkat) vlate = add(1, lp, 0, 1);
        c1[n1++] = add(0, pr, (sc.l2 >> (2 * pr)) & 1);
        c1[n1++] = pr == lp ? vlate : add(1, pr, (sc.l2 >> (2 * pr + 1)) & 1);
    }
    auto tile_of = [&](int it) { return 2 * items[it].tile + items[it].map; };
    auto keep1 = [&](int it) { return items[it].tile >= NRF && items[it].tile <= lp; };
    const int tail1 = n;
    add(M_WOA, 0, sc.promoW & 1);
    add(M_WQB, 0, sc.promoB & 1);
    for (int u = 0; u < 4; u++) add(M_KB + (u >> 1), u & 1, (sc.promoB >> (1 + u)) & 1);
    add(M_WOB, 0, (sc.promoB >> 5) & 1);
    add(M_WQA, 0, 0);
    for (int sp = 0; sp < 16; sp++) {
        const int pr = (sc.ord3 >> (60 - 4 * sp)) & 15;
        for (int u = 2 * pr; u < 2 * pr + 2; u++) {
            int it = -1;
            for (int i = 0; i < n1; i++) if (keep1(c1[i]) && tile_of(c1[i]) == u) it = c1[i];
            c3[n3++] = pr < NRF ? -1 - u : (it >= 0 ? it : add(u & 1, u >> 1, 0));
        }
    }
    const int tail3 = n;
    add(M_WOA, 0, 0); add(M_WQB, 0, 0);
    for (int u = 0; u < 4; u++) add(M_KB + (u >> 1), u & 1, 0);
    add(M_WOB, 0, 0);
    int slot_of[96], pending[96] = {0}, fre[16], nfree = 0, par[NSLOT] = {0}, ic = NFIRST, c = 0, nq = NFIRST, reserve = 0;
    for (int i = 0; i < NFIRST; i++) { slot_of[i] = i; pending[i] = 1; }
    for (int i = NSLOT - 1; i >= NFIRST; i--) fre[nfree++] = i;
    for (int i = 0; i < NSTEP; i++) p.steps[i] = 0;
    auto load = [&](int depth) -> uint32_t {
        if (!(ic < n && nfree > reserve && nq < depth)) return 0;
        const Item& it = items[ic];
        const int dst = slot_of[ic] = fre[--nfree];
        if (!it.park) { pending[ic] = 1; nq++; }
        ic++;
        return 16 | (it.promote << 5) | (it.map << 6) | (it.tile << 9) | (dst << 16);
    };
    int pc = 0, pfd = 0;
    auto load_or_pf = [&](int depth) -> uint32_t {
        uint32_t e = load(depth);
        if (pc < ic) pc = ic;
        if (!e && pc < n && nq + (pc - ic) < pfd) { e = 32 | (items[pc].map << 6) | (items[pc].tile << 9); pc++; }
        return e;
    };
    auto extra = [&](int depth) { p.steps[c++] = load_or_pf(depth); };
    auto release = [&](int slot) { par[slot] ^= 1; fre[nfree++] = slot; };
    auto consume = [&](int it, bool keep) -> uint32_t {
        const int slot = slot_of[it];
        if (pending[it]) { pending[it] = 0; nq--; }
        const uint32_t e = slot | (par[slot] << 3);
        if (!keep) release(slot);
        return e;
    };
    auto step = [&](int it, bool keep, int depth) { const uint32_t e = consume(it, keep); p.steps[c++] = e | load_or_pf(depth); };
    auto atleast1 = [](int d) { return d < 1 ? 1 : d; };
    int layer = 0;
    auto chain = [&](int t0, bool keep0, int t1, bool keep1_, int wo, int wq, int d, int pf) {
        reserve = keep1_ ? 1 : 0;
        pfd = dig(pf, 0) - 1;
        step(t0, keep0, atleast1(dig(d, 0)));
        reserve = 0;
        p.steps[c++] = consume(t1, keep1_) | STEP_LAST;
        p.last[layer++] = c - 1;
        const int scratch = fre[nfree - 1];
        pfd = dig(pf, 1);
        extra(atleast1(dig(d, 1))); p.steps[c - 1] |= scratch;
        extra(dig(d, 1));
        const int at = c++;
        pfd = dig(pf, 2);
        extra(dig(d, 2));
        p.steps[at] = consume(wo, false);
        pfd = dig(pf, 3);
        p.steps[at] |= load_or_pf(atleast1(dig(d, 3)));
        extra(dig(d, 3));
        if (wq < 0) return;
        p.first[layer] = c;
        pfd = dig(pf, 4);
        step(wq, false, dig(d, 4));
        pfd = dig(pf, 5);
        extra(dig(d, 5));
        pfd = dig(pf, 6);
        extra(atleast1(dig(d, 6))); extra(dig(d, 6));
        pfd = 0;
    };
    p.first[0] = 0;
    step(wq1, false, 0); extra(0); extra(sc.d0); extra(sc.d0);
    for (int u = 0; u < 30; u++) {
        if (late && u == 29) { reserve = 1; pfd = dig(sc.pf1, 0) - 1; }
        const int depth = u < 2 ? sc.d0 : (u < nearly ? sc.dr : sc.d1), pr = items[c1[u]].tile;
        if (pr < NRF) {
            step(c1[u], true, depth);
            if (u & 1) { release(slot_of[c1[u - 1]]); release(slot_of[c1[u]]); } else p.steps[c - 1] |= STEP_RF | (pr << 21);
        } else step(c1[u], keep1(c1[u]), depth);
    }
    chain(c1[30], keep1(c1[30]), c1[31], keep1(c1[31]), tail1, tail1 + 1, sc.ch1, sc.pf1);
    step(tail1 + 2, false, atleast1(dig(sc.ch1, 7))); step(tail1 + 3, false, atleast1(dig(sc.ch1, 8)));
    chain(tail1 + 4, false, tail1 + 5, false, tail1 + 6, tail1 + 7, sc.ch2, sc.pf2);
    for (int u = 0; u < n3 - 2; u++) {
        int left = 0;
        for (int i = u + 1; i < n3; i++) left += c3[i] >= 0;
        const int cap = left + dig(sc.ch3, 0) - 1, depth = sc.d3 < cap ? sc.d3 : cap;
        const int nxt = (u | 1) + 1;
        reserve = nxt < n3 && c3[nxt] < 0 ? ((u & 1) ? 2 : 1) : 0;
        if (c3[u] < 0) {
            const int sk = fre[--nfree], sv = fre[--nfree];
            uint32_t e = sk | (par[sk] << 3) | STEP_RF | (((-1 - c3[u]) >> 1) << 21);
            release(sk); p.steps[c++] = e | load(depth);
            u++;
            reserve = nxt < n3 && c3[nxt] < 0 ? 2 : 0;
            e = sv | (par[sv] << 3);
            release(sv); p.steps[c++] = e | load(depth);
        } else step(c3[u], false, depth);
    }
    reserve = 0;
    chain(c3[n3 - 2], false, c3[n3 - 1], false, tail3, tail3 + 1, sc.ch3, 0);
    step(tail3 + 2, false, atleast1(dig(sc.ch3, 7))); step(tail3 + 3, false, atleast1(dig(sc.ch3, 8)));
    chain(tail3 + 4, false, tail3 + 5, false, tail3 + 6, -1, 777777777, 0);
}

Sched g_sched;

}

extern "C" void kernel_launch(void* const* d_in, const int* in_sizes, int n_in, void* d_out, int out_size) {
    (void)in_sizes; (void)n_in; (void)out_size;
    void* fn = nullptr;
    cudaDriverEntryPointQueryResult qr;
    cudaGetDriverEntryPoint("cuTensorMapEncodeTiled", &fn, cudaEnableDefault, &qr);
    EncodeFn enc = (EncodeFn)fn;
    Params p;
    const CUtensorMapL2promotion pk = CU_TENSOR_MAP_L2_PROMOTION_L2_256B, pw = CU_TENSOR_MAP_L2_PROMOTION_NONE;
    const size_t win = (size_t)28672 * 256;
    encode5d(enc, &p.maps[M_KA], d_in[1], 64, 32, 128, 128, 4096, 512 << 10, 8 << 20, CU_TENSOR_MAP_SWIZZLE_128B, pk);
    encode5d(enc, &p.maps[M_VA], d_in[2], 64, 32, 128, 128, 4096, 512 << 10, 8 << 20, CU_TENSOR_MAP_SWIZZLE_128B, pk);
    encode5d(enc, &p.maps[M_KB], (const char*)d_in[6] + win, 64, 32, 16, 128, 4096, 64 << 10, 8 << 20, CU_TENSOR_MAP_SWIZZLE_128B, pk);
    encode5d(enc, &p.maps[M_VB], (const char*)d_in[7] + win, 64, 32, 16, 128, 4096, 64 << 10, 8 << 20, CU_TENSOR_MAP_SWIZZLE_128B, pk);
    encode5d(enc, &p.maps[M_WQA], d_in[3], 32, 64, 8, 8192, 64 * 8192, 64, 1024, CU_TENSOR_MAP_SWIZZLE_64B, pw);
    encode5d(enc, &p.maps[M_WQB], d_in[8], 32, 64, 8, 8192, 64 * 8192, 64, 1024, CU_TENSOR_MAP_SWIZZLE_64B, pw);
    encode5d(enc, &p.maps[M_WOA], d_in[4], 32, 64, 8, 1024, 64 << 10, 64, 512 << 10, CU_TENSOR_MAP_SWIZZLE_64B, pw);
    encode5d(enc, &p.maps[M_WOB], d_in[9], 32, 64, 8, 1024, 64 << 10, 64, 512 << 10, CU_TENSOR_MAP_SWIZZLE_64B, pw);
    void* xc = nullptr;
    cudaGetSymbolAddress(&xc, g_xchg);
    p.xc = (Xchg*)xc;
    p.x = (const __nv_bfloat16*)d_in[0];
    p.out = (__nv_bfloat16*)d_out;
    build_schedule(p, g_sched);
    cudaFuncSetAttribute(decode_kernel, cudaFuncAttributeMaxDynamicSharedMemorySize, SMEM_BYTES);
    decode_kernel<<<NCTA, NW * 32, SMEM_BYTES, cudaStreamPerThread>>>(p);
}
```

```cpp
#include <cuda_runtime.h>
#include <cuda_bf16.h>
#include <cuda.h>
#include <stdint.h>

namespace {

constexpr int NCTA  = 128;
constexpr int NW    = 8;
constexpr int NSLOT = 7;
constexpr int TILE  = 4096;
constexpr int NFIRST = 3;
constexpr int NRF = 4;

constexpr int OFF_BAR = NW * NSLOT * TILE;
constexpr int OFF_RED = OFF_BAR + 512;
constexpr int OFF_ST  = OFF_RED + 2048;
constexpr int OFF_ML  = OFF_ST + 64;
constexpr int OFF_META = OFF_ML + 256;
constexpr int SMEM_BYTES = OFF_META + 128;

constexpr uint64_t POL_EVICT_FIRST = 0x12F0000000000000ull;
constexpr int SPIN_LIMIT = 1 << 20;
constexpr unsigned FULL = 0xffffffffu;

enum { M_KA = 0, M_VA = 1, M_KB = 2, M_VB = 3, M_WQA = 4, M_WQB = 5, M_WOA = 6, M_WOB = 7 };

constexpr uint32_t STEP_LAST = 1u << 13, STEP_PACK = 1u << 20, STEP_TOREG = 1u << 14, STEP_FENCE = 1u << 15;
constexpr int NSTEP = 120;
struct Xchg {
    float q[NCTA][32];
    float part[NCTA][NW][96];
    float x[2][NCTA][32];
};
struct __align__(64) Params {
    CUtensorMap maps[8];
    const __nv_bfloat16* x;
    __nv_bfloat16* out;
    Xchg* xc;
    uint32_t post[2][8][2];
    int first[4], last[4];
    uint32_t steps[NSTEP];
};
__device__ __align__(128) Xchg g_xchg;
#define TSTAMP(i)

__device__ __forceinline__ int lane_id() { int l; asm volatile("mov.u32 %0, %%laneid;" : "=r"(l)); return l; }
__device__ __forceinline__ bool mbar_try(uint32_t bar, uint32_t parity) {
    uint32_t ok;
    asm volatile("{\n.reg .pred p;\nmbarrier.try_wait.parity.shared::cta.b64 p, [%1], %2;\nselp.u32 %0, 1, 0, p;\n}"
                 : "=r"(ok) : "r"(bar), "r"(parity) : "memory");
    return __all_sync(0xffffffffu, ok);
}
__device__ __forceinline__ bool mbar_test(uint32_t bar, uint32_t parity) {
    uint32_t ok;
    asm volatile("{\n.reg .pred p;\nmbarrier.test_wait.parity.shared::cta.b64 p, [%1], %2;\nselp.u32 %0, 1, 0, p;\n}"
                 : "=r"(ok) : "r"(bar), "r"(parity) : "memory");
    return __all_sync(0xffffffffu, ok);
}
__device__ __forceinline__ void mbar_wait(uint32_t bar, uint32_t parity) {
    if (!mbar_try(bar, parity)) {
        int n = 0;
        while (!mbar_try(bar, parity) && ++n < (1 << 17)) {}
    }
}
__device__ __forceinline__ void ldsm4(uint32_t* r, uint32_t a) {
    asm volatile("ldmatrix.sync.aligned.m8n8.x4.shared.b16 {%0,%1,%2,%3}, [%4];"
                 : "=r"(r[0]), "=r"(r[1]), "=r"(r[2]), "=r"(r[3]) : "r"(a) : "memory");
}
__device__ __forceinline__ void ldsm4t(uint32_t* r, uint32_t a) {
    asm volatile("ldmatrix.sync.aligned.m8n8.x4.trans.shared.b16 {%0,%1,%2,%3}, [%4];"
                 : "=r"(r[0]), "=r"(r[1]), "=r"(r[2]), "=r"(r[3]) : "r"(a) : "memory");
}
__device__ __forceinline__ void mma16816(float* c, uint32_t a0, uint32_t a1, uint32_t a2, uint32_t a3, uint32_t b0, uint32_t b1) {
    asm volatile("mma.sync.aligned.m16n8k16.row.col.f32.bf16.bf16.f32 {%0,%1,%2,%3}, {%4,%5,%6,%7}, {%8,%9}, {%0,%1,%2,%3};"
                 : "+f"(c[0]), "+f"(c[1]), "+f"(c[2]), "+f"(c[3])
                 : "r"(a0), "r"(a1), "r"(a2), "r"(a3), "r"(b0), "r"(b1));
}
__device__ __forceinline__ void mma16816(float* c, const uint32_t* a, uint32_t b0, uint32_t b1) { mma16816(c, a[0], a[1], a[2], a[3], b0, b1); }
__device__ __forceinline__ uint32_t movm(uint32_t a) {
    uint32_t d;
    asm volatile("movmatrix.sync.aligned.m8n8.trans.b16 %0, %1;" : "=r"(d) : "r"(a));
    return d;
}
__device__ __forceinline__ uint32_t pack_bf16(float lo, float hi) {
    uint32_t d;
    asm("cvt.rn.bf16x2.f32 %0, %1, %2;" : "=r"(d) : "f"(hi), "f"(lo));
    return d;
}
__device__ __forceinline__ float bf_lo(uint32_t v) { return __uint_as_float(v << 16); }
__device__ __forceinline__ float bf_hi(uint32_t v) { return __uint_as_float(v & 0xffff0000u); }
__device__ __forceinline__ float ex2(float v) { float d; asm("ex2.approx.ftz.f32 %0, %1;" : "=f"(d) : "f"(v)); return d; }
__device__ __forceinline__ float rcp(float v) { float d; asm("rcp.approx.ftz.f32 %0, %1;" : "=f"(d) : "f"(v)); return d; }
__device__ __forceinline__ float rsq(float v) { float d; asm("rsqrt.approx.ftz.f32 %0, %1;" : "=f"(d) : "f"(v)); return d; }
__device__ __forceinline__ uint32_t tagged(float v, uint32_t tag) { return (__float_as_uint(v) & ~3u) | tag; }

__device__ __forceinline__ void st_rlx8(void* p, uint32_t a, uint32_t b) {
    asm volatile("{\n.reg .b64 l;\nmov.b64 l, {%1,%2};\nst.relaxed.gpu.global.b64 [%0], l;\n}" :: "l"(p), "r"(a), "r"(b) : "memory");
}
__device__ __forceinline__ void ld_rlx8(uint32_t& a, uint32_t& b, const void* p) {
    asm volatile("{\n.reg .b64 l;\nld.relaxed.gpu.global.b64 l, [%2];\nmov.b64 {%0,%1}, l;\n}" : "=r"(a), "=r"(b) : "l"(p) : "memory");
}
__device__ __forceinline__ void st_rlx16(void* p, uint32_t a, uint32_t b, uint32_t c, uint32_t d) {
    asm volatile("{\n.reg .b64 l, h;\n.reg .b128 v;\nmov.b64 l, {%1,%2};\nmov.b64 h, {%3,%4};\nmov.b128 v, {l,h};\n"
                 "st.relaxed.gpu.global.b128 [%0], v;\n}" :: "l"(p), "r"(a), "r"(b), "r"(c), "r"(d) : "memory");
}
__device__ __forceinline__ void ld_rlx16(uint32_t* r, const void* p) {
    asm volatile("{\n.reg .b64 l, h;\n.reg .b128 v;\nld.relaxed.gpu.global.b128 v, [%4];\nmov.b128 {l,h}, v;\n"
                 "mov.b64 {%0,%1}, l;\nmov.b64 {%2,%3}, h;\n}" : "=r"(r[0]), "=r"(r[1]), "=r"(r[2]), "=r"(r[3]) : "l"(p) : "memory");
}
__device__ __forceinline__ void sts(uint32_t a, float v) { asm volatile("st.shared.f32 [%0], %1;" :: "r"(a), "f"(v) : "memory"); }
__device__ __forceinline__ void sts2(uint32_t a, float x, float y) { asm volatile("st.shared.v2.f32 [%0], {%1,%2};" :: "r"(a), "f"(x), "f"(y) : "memory"); }
__device__ __forceinline__ void lds4(float* v, uint32_t a) { asm volatile("ld.shared.v4.f32 {%0,%1,%2,%3}, [%4];" : "=f"(v[0]), "=f"(v[1]), "=f"(v[2]), "=f"(v[3]) : "r"(a) : "memory"); }

constexpr float SCALE_LOG2E = 0.08838834764831845f * 1.4426950408889634f;
constexpr float MAX_SLACK = 8.f;

__device__ __forceinline__ uint32_t slot_addr(uint32_t wslots, uint32_t e) { return wslots + (e & 7u) * TILE; }
__device__ __forceinline__ uint32_t slot_bar(uint32_t wbars, uint32_t e) { return wbars + (e & 7u) * 8; }
__device__ __forceinline__ void wait_step(uint32_t wbars, uint32_t e) { mbar_wait(slot_bar(wbars, e), (e >> 3) & 1u); }
__device__ __forceinline__ void refill(const Params& p, uint32_t e, uint32_t wslots, uint32_t wbars, int w) {
    const unsigned char* m = reinterpret_cast<const unsigned char*>(&p.maps[0]) + ((e << 1) & 0x380u);
    const int c2 = w + ((e >> 6) & 0x78u), c3 = blockIdx.x & 15, c4 = blockIdx.x >> 4;
    asm volatile("{\n.reg .pred p, q;\n"
                 "elect.sync _|p, 0xffffffff;\n"
                 "setp.ne.and.u32 q, %9, 0, p;\n"
                 "setp.ne.and.u32 p, %8, 0, p;\n"
                 "@p mbarrier.arrive.expect_tx.shared::cta.b64 _, [%6], 4096;\n"
                 "@p cp.async.bulk.tensor.5d.shared::cluster.global.mbarrier::complete_tx::bytes.L2::cache_hint [%0], [%1, {%2,%2,%3,%4,%5}], [%6], %7;\n"
                 "@q cp.async.bulk.prefetch.tensor.5d.L2.global.tile [%1, {%2,%2,%3,%4,%5}];\n"
                 "}"
                 :: "r"(slot_addr(wslots, e >> 16)), "l"(m), "r"(0), "r"(c2), "r"(c3), "r"(c4), "r"(slot_bar(wbars, e >> 16)), "l"(POL_EVICT_FIRST),
                    "r"(e & 16u), "r"(e & 32u) : "memory");
}

__device__ __forceinline__ void refill_if(const Params& p, uint32_t e, uint32_t wslots, uint32_t wbars, int w) {
    if (e & 48u) refill(p, e, wslots, wbars, w);
}
template <class T> __device__ __forceinline__ T* pin(T* q) { asm volatile("" : "+l"(q)); return q; }
__device__ __forceinline__ uint32_t pin(uint32_t v) { asm volatile("" : "+r"(v)); return v; }
__device__ __forceinline__ float selp(float a, float b, bool c) {
    float d;
    asm("{\n.reg .pred p;\nsetp.ne.u32 p, %3, 0;\nselp.f32 %0, %1, %2, p;\n}" : "=f"(d) : "f"(a), "f"(b), "r"((uint32_t)c));
    return d;
}

constexpr uint32_t SWAP = 0x90;
struct Attn {
    uint32_t qf[8];
    float o[16];
    float n0, n1;
    float l0, l1;
    uint32_t mv;
};
__device__ __forceinline__ void load_k(uint32_t* f, uint32_t base) {
#pragma unroll
    for (int j = 0; j < 4; j++) {
        ldsm4(f + 8 * j, base ^ (j << 5));
        ldsm4(f + 8 * j + 4, (base ^ (j << 5) ^ SWAP) + 2048);
    }
}
__device__ __forceinline__ void load_v(uint32_t* f, uint32_t base) {
#pragma unroll
    for (int j = 0; j < 4; j++) ldsm4t(f + 8 * j, base ^ (j << 5));
#pragma unroll
    for (int j = 0; j < 4; j++) ldsm4t(f + 8 * j + 4, (base ^ (j << 5) ^ SWAP) + 2048);
}
__device__ __forceinline__ void qk(const Attn& a, const uint32_t* f, float* s) {
    float c[8];
#pragma unroll
    for (int i = 0; i < 8; i++) c[i] = 0.f;
#pragma unroll
    for (int j = 0; j < 4; j++) {
        mma16816(c, f + 8 * j, a.qf[2 * j], a.qf[2 * j + 1]);
        mma16816(c + 4, f + 8 * j + 4, a.qf[2 * j], a.qf[2 * j + 1]);
    }
#pragma unroll
    for (int i = 0; i < 4; i++) s[i] = __uint_as_float((__float_as_uint(c[i]) & a.mv) | (__float_as_uint(c[i + 4]) & ~a.mv));
}
__device__ __forceinline__ void pv(Attn& a, const uint32_t* f, const uint32_t* b) {
#pragma unroll
    for (int j = 0; j < 4; j++) mma16816(a.o + 4 * j, f + 8 * j, b[0], b[1]);
#pragma unroll
    for (int j = 0; j < 4; j++) mma16816(a.o + 4 * j, f + 8 * j + 4, b[2], b[3]);
}
__device__ __forceinline__ void probs(const Attn& a, const float* y, uint32_t* b, float& l0, float& l1) {
    float e[4];
#pragma unroll
    for (int i = 0; i < 4; i++) e[i] = ex2(y[i]);
    const uint32_t p0 = pack_bf16(e[0], e[1]), p1 = pack_bf16(e[2], e[3]);
    b[0] = movm(p0 & a.mv); b[1] = movm(p1 & a.mv);
    b[2] = movm(p0 & ~a.mv); b[3] = movm(p1 & ~a.mv);
    l0 = a.l0 + (e[0] + e[2]);
    l1 = a.l1 + (e[1] + e[3]);
}
__device__ __forceinline__ void softmax_step(Attn& a, float* s, uint32_t* b) {
    float y[4], l0, l1;
#pragma unroll
    for (int i = 0; i < 4; i++) s[i] += __shfl_xor_sync(FULL, s[i], 6);
#pragma unroll
    for (int i = 0; i < 4; i++) y[i] = fmaf(s[i], SCALE_LOG2E, (i & 1) ? a.n1 : a.n0);
    probs(a, y, b, l0, l1);
    if (__any_sync(FULL, fmaxf(fmaxf(y[0], y[1]), fmaxf(y[2], y[3])) > MAX_SLACK)) {
        float t0 = fmaxf(s[0], s[2]), t1 = fmaxf(s[1], s[3]);
#pragma unroll
        for (int d = 4; d <= 16; d <<= 1) {
            t0 = fmaxf(t0, __shfl_xor_sync(FULL, t0, d));
            t1 = fmaxf(t1, __shfl_xor_sync(FULL, t1, d));
        }
        t0 = fminf(-SCALE_LOG2E * t0, a.n0); t1 = fminf(-SCALE_LOG2E * t1, a.n1);
        const float r0 = ex2(t0 - a.n0), r1 = ex2(t1 - a.n1);
        a.n0 = t0; a.n1 = t1;
        a.l0 *= r0; a.l1 *= r1;
#pragma unroll
        for (int i = 0; i < 16; i += 2) { a.o[i] *= r0; a.o[i + 1] *= r1; }
#pragma unroll
        for (int i = 0; i < 4; i++) y[i] = fmaf(s[i], SCALE_LOG2E, (i & 1) ? a.n1 : a.n0);
        probs(a, y, b, l0, l1);
    }
    a.l0 = l0; a.l1 = l1;
}

constexpr uint32_t NOPATCH = 0xffffffffu, B87 = 0x87878787u;
__device__ __forceinline__ void lds4u(uint32_t* v, uint32_t a) { asm volatile("ld.shared.v4.u32 {%0,%1,%2,%3}, [%4];" : "=r"(v[0]), "=r"(v[1]), "=r"(v[2]), "=r"(v[3]) : "r"(a) : "memory"); }
__device__ __forceinline__ void sts4u(uint32_t a, const uint32_t* v) { asm volatile("st.shared.v4.u32 [%0], {%1,%2,%3,%4};" :: "r"(a), "r"(v[0]), "r"(v[1]), "r"(v[2]), "r"(v[3]) : "memory"); }
__device__ __forceinline__ void sts_u8(uint32_t a, uint32_t v) { asm volatile("st.shared.u8 [%0], %1;" :: "r"(a), "r"(v) : "memory"); }
__device__ __forceinline__ void sts_u16(uint32_t a, uint32_t v) { asm volatile("st.shared.u16 [%0], %1;" :: "r"(a), "r"(v) : "memory"); }
__device__ __forceinline__ uint32_t lds_u16(uint32_t a) { uint32_t v; asm volatile("ld.shared.u16 %0, [%1];" : "=r"(v) : "r"(a) : "memory"); return v; }
__device__ __forceinline__ uint32_t lds_u32(uint32_t a) { uint32_t v; asm volatile("ld.shared.u32 %0, [%1];" : "=r"(v) : "r"(a) : "memory"); return v; }
__device__ __forceinline__ uint32_t bitsel(uint32_t a, uint32_t b, uint32_t m) {
    uint32_t d;
    asm("lop3.b32 %0, %1, %2, %3, 0xE4;" : "=r"(d) : "r"(a), "r"(b), "r"(m));
    return d;
}
__device__ __forceinline__ uint32_t mul2(uint32_t a, uint32_t b) { uint32_t d; asm("mul.rn.bf16x2 %0, %1, %2;" : "=r"(d) : "r"(a), "r"(b)); return d; }

__device__ __forceinline__ void pack_tile(uint32_t src, uint32_t dst, uint32_t meta, uint32_t id, uint32_t& patch, int lane) {
    src += lane * 16; dst += lane * 16;
    uint32_t m0 = 0, m1 = 0;
#pragma unroll
    for (int k = 0; k < 8; k++) {
        uint32_t r[4];
        lds4u(r, src + k * 512);
        asm("max.xorsign.abs.bf16x2 %0, %0, %1;" : "+r"(m0) : "r"(r[0]));
        asm("max.xorsign.abs.bf16x2 %0, %0, %1;" : "+r"(m1) : "r"(r[1]));
        asm("max.xorsign.abs.bf16x2 %0, %0, %1;" : "+r"(m0) : "r"(r[2]));
        asm("max.xorsign.abs.bf16x2 %0, %0, %1;" : "+r"(m1) : "r"(r[3]));
    }
    asm("max.xorsign.abs.bf16x2 %0, %0, %1;" : "+r"(m0) : "r"(m1));
    const int top = __reduce_max_sync(FULL, (int)max((m0 >> 23) & 0xffu, (m0 >> 7) & 0xffu));
    uint32_t sh = min(max(top - 15, 0), 126);
    const uint32_t up = (127u + sh) * 0x00800080u, down = (127u - sh) * 0x00800080u;
#pragma unroll 1
    for (int hf = 0; hf < 2; hf++) {
        uint32_t o[12], bad = 0;
#pragma unroll
        for (int k = 0; k < 4; k++) {
            uint32_t r[4], s[4];
            lds4u(r, src + hf * 2048 + k * 512);
#pragma unroll
            for (int i = 0; i < 4; i++) s[i] = mul2(r[i], down);
            o[3 * k] = __byte_perm(s[0], s[1], 0x6420);
            o[3 * k + 1] = __byte_perm(s[2], s[3], 0x6420);
            const uint32_t h0 = __byte_perm(s[0], s[1], 0x7531), h1 = __byte_perm(s[2], s[3], 0x7531);
            o[3 * k + 2] = bitsel(h1, __funnelshift_l(h0, h0, 4), B87);
            uint32_t d = (h0 | h1) & ~B87;
#pragma unroll
            for (int i = 0; i < 4; i++) d |= mul2(s[i], up) ^ r[i];
            if (d) bad |= 15u << (4 * k);
        }
        bad = __reduce_or_sync(FULL, bad);
#pragma unroll 1
        for (; bad != 0u && sh != 0xffu; bad &= bad - 1u) {
            const int k = __ffs(bad) - 1;
            const uint32_t at = hf * 2048 + (k >> 2) * 512 + (k & 3) * 4;
            const uint32_t r = lds_u32(src + at);
            uint32_t b = mul2(mul2(r, down) & 0x87ff87ffu, up) ^ r;
#pragma unroll 1
            for (uint32_t lanes; (lanes = __ballot_sync(FULL, b != 0u)) != 0u;) {
                const int n = __popc(__ballot_sync(FULL, patch != NOPATCH));
                if (n == 32) {
                    sh = 0xffu;
                    if ((patch >> 28) == id) patch = NOPATCH;
                    break;
                }
                const uint32_t hi = (b & 0xffffu) ? 0u : 16u;
                const int from = __ffs(lanes) - 1;
                const uint32_t ent = __shfl_sync(FULL, (id << 28) | ((at + lane * 16 + (hi >> 3)) << 16) | ((r >> hi) & 0xffffu), from);
                if (lane == n) patch = ent;
                if (lane == from) b &= ~(0xffffu << hi);
            }
        }
#pragma unroll
        for (int j = 0; j < 3; j++) sts4u(dst + hf * 1536 + j * 512, o + 4 * j);
    }
    if (lane == 0) sts_u8(meta, sh);
}
__device__ __forceinline__ void unpack_tile(const uint32_t* o, uint32_t dst, uint32_t up) {
#pragma unroll
    for (int k = 0; k < 8; k++) {
        const uint32_t n = o[3 * k + 2];
        const uint32_t h0 = __funnelshift_r(n, n, 4) & B87, h1 = n & B87;
        uint32_t r[4];
        r[0] = mul2(__byte_perm(o[3 * k], h0, 0x5140), up); r[1] = mul2(__byte_perm(o[3 * k], h0, 0x7362), up);
        r[2] = mul2(__byte_perm(o[3 * k + 1], h1, 0x5140), up); r[3] = mul2(__byte_perm(o[3 * k + 1], h1, 0x7362), up);
        sts4u(dst + k * 512, r);
    }
}

__device__ __forceinline__ uint32_t add_residual(uint32_t xp, const uint32_t (*v)[4], bool half) {
    float r[4];
#pragma unroll
    for (int k = 0; k < 4; k++)
        r[k] = (__uint_as_float(v[0][k]) + __uint_as_float(v[1][k])) + (__uint_as_float(v[2][k]) + __uint_as_float(v[3][k]));
    const float y0 = selp(r[2], r[0], half) + __shfl_xor_sync(FULL, selp(r[0], r[2], half), 16);
    const float y1 = selp(r[3], r[1], half) + __shfl_xor_sync(FULL, selp(r[1], r[3], half), 16);
    const uint32_t yb = pack_bf16(y0, y1);
    return pack_bf16(bf_lo(xp) + bf_lo(yb), bf_hi(xp) + bf_hi(yb));
}

__device__ __forceinline__ void gemv_load(uint32_t (*f)[4], uint32_t tile, int lane) {
    const int mi = lane >> 3, r = lane & 7;
    const uint32_t a0 = tile + ((mi >> 1) * 8 + r) * 64 + (((mi & 1) ^ (r >> 1)) << 4);
#pragma unroll
    for (int j = 0; j < 4; j++) {
        ldsm4t(f[2 * j], a0 + j * 1024);
        ldsm4t(f[2 * j + 1], (a0 ^ 32u) + j * 1024);
    }
}
template <bool STATS>
__device__ __forceinline__ void gemv_mma(const uint32_t (*f)[4], uint32_t vpair, float& y0, float& y1, float* st, int lane) {
    const int src = ((lane >> 1) & 1) + 16 * (lane & 1);
    float c[4][4];
    uint32_t x[8];
#pragma unroll
    for (int j = 0; j < 8; j++) x[j] = __shfl_sync(FULL, vpair, 2 * j + src);
#pragma unroll
    for (int i = 0; i < 4; i++) { c[0][i] = c[1][i] = c[2][i] = c[3][i] = 0.f; if (STATS) st[i] = 0.f; }
#pragma unroll
    for (int j = 0; j < 4; j++) {
        uint32_t b0 = x[2 * j], b1 = x[2 * j + 1];
        if (STATS && (lane & 4)) b0 = b1 = 0x3f803f80u;
        mma16816(c[2 * (j & 1)], f[2 * j], b0, b1);
        mma16816(c[2 * (j & 1) + 1], f[2 * j + 1], b0, b1);
        if (STATS) mma16816(st, x[2 * j], x[2 * j], x[2 * j + 1], x[2 * j + 1], b0, b1);
    }
    const bool t1 = lane & 1, t2 = lane & 2;
    y0 = selp(selp(c[1][2] + c[3][2], c[1][0] + c[3][0], t1), selp(c[0][2] + c[2][2], c[0][0] + c[2][0], t1), t2);
    if (STATS) y1 = selp(selp(c[1][3] + c[3][3], c[1][1] + c[3][1], t1), selp(c[0][3] + c[2][3], c[0][1] + c[2][1], t1), t2);
}

__global__ void __launch_bounds__(NW * 32, 1)
decode_kernel(const __grid_constant__ Params p) {
    extern __shared__ __align__(1024) unsigned char smem_raw[];
    const uint32_t smem = (uint32_t)__cvta_generic_to_shared(smem_raw);
    int lane = lane_id();
    const int w = __shfl_sync(FULL, threadIdx.x >> 5, 0);
    const int cta = blockIdx.x, h = cta >> 4;
    const uint32_t wslots = smem + w * (NSLOT * TILE);
    const uint32_t wbars = smem + OFF_BAR + w * (NSLOT * 8);
    TSTAMP(0);
    if (lane < NSLOT) {
        asm volatile("mbarrier.init.shared::cta.b64 [%0], 1;" :: "r"(wbars + lane * 8) : "memory");
        asm volatile("fence.proxy.async.shared::cta;" ::: "memory");
    }
    __syncwarp();
    refill(p, 16 | (M_WQA << 6), wslots, wbars, w);
#pragma unroll
    for (int i = 1; i < NFIRST; i++) refill(p, (i << 16) | 16 | (((i - 1) & 1) << 6) | (((i - 1) >> 1) << 9), wslots, wbars, w);
    uint32_t xp = reinterpret_cast<const uint32_t*>(p.x)[32 * w + 2 * (lane & 15) + (lane >> 4)];
    TSTAMP(1);

    uint32_t rf[2 * NRF][24];
    uint32_t patch = NOPATCH;
#pragma unroll
    for (int i = 0; i < 2 * NRF; i++)
#pragma unroll
        for (int j = 0; j < 24; j++) rf[i][j] = 0u;

#pragma unroll 1
    for (int layer = 0; layer < 4; layer++) {
        const uint32_t tag = (layer + 1) & 3;
        int c = p.first[layer];
        Attn a;
        {
            const uint32_t e = p.steps[c];
            const int half = lane >> 4;
            const uint32_t ptag = layer & 3;
            const float* src = pin(&p.xc->x[(layer + 1) & 1][16 * half + 2 * w][4 * (lane & 15)]);
            uint32_t v[4][4], f[8][4];
            if (layer > 0) {
#pragma unroll
                for (int j = 0; j < 4; j++) ld_rlx16(v[j], src + j * 1024);
            } else {
#pragma unroll
                for (int j = 0; j < 4; j++) v[j][0] = v[j][1] = v[j][2] = v[j][3] = 0u;
            }
            wait_step(wbars, e);
            gemv_load(f, slot_addr(wslots, e), lane);
            asm volatile("" :: "r"(f[7][3]), "r"(f[6][3]) : "memory");
            refill_if(p, e, wslots, wbars, w);
            if (layer > 0) {
                int it = 0;
                while (!__all_sync(FULL, (((v[0][0] ^ ptag) | (v[1][0] ^ ptag) | (v[2][0] ^ ptag) | (v[3][0] ^ ptag)) & 3u) == 0u) && ++it < SPIN_LIMIT) {
#pragma unroll
                    for (int j = 0; j < 4; j++)
                        if ((v[j][0] ^ ptag) & 3u) ld_rlx16(v[j], src + j * 1024);
                }
                xp = add_residual(xp, v, half);
                TSTAMP(layer * 8);
            }
            refill_if(p, p.steps[c + 1], wslots, wbars, w);
            float y0, y1, st[4];
            gemv_mma<true>(f, xp, y0, y1, st, lane);
            float* dst = pin(&p.xc->q[cta][2 * lane]);
            sts2(smem + OFF_RED + w * 256 + (8 * (lane & 3) + (lane >> 2)) * 8, y0, y1);
            if (lane == 0) sts2(smem + OFF_ST + w * 8, st[0], st[1]);
            __syncthreads();
            if (w == 0) {
                float u[8][4], z[16];
#pragma unroll
                for (int i = 0; i < 4; i++) lds4(z + 4 * i, smem + OFF_ST + 16 * i);
#pragma unroll
                for (int i = 0; i < 8; i++) lds4(u[i], smem + OFF_RED + i * 256 + (lane & 15) * 16);
                const float sq = ((z[0] + z[2]) + (z[4] + z[6])) + ((z[8] + z[10]) + (z[12] + z[14]));
                const float su = ((z[1] + z[3]) + (z[5] + z[7])) + ((z[9] + z[11]) + (z[13] + z[15]));
                const float mean = su * (1.f / 512.f);
                const float rstd = rsq(fmaxf(fmaf(-mean, mean, sq * (1.f / 512.f)), 0.f) + 1e-5f);
                float r[4];
#pragma unroll
                for (int k = 0; k < 4; k++) r[k] = ((u[0][k] + u[1][k]) + (u[2][k] + u[3][k])) + ((u[4][k] + u[5][k]) + (u[6][k] + u[7][k]));
                if (lane < 16) st_rlx8(dst, tagged(fmaf(-mean, r[1], r[0]) * rstd, tag), __float_as_uint(fmaf(-mean, r[3], r[2]) * rstd));
            }
            TSTAMP(2 + layer * 8);
            refill_if(p, p.steps[c + 2], wslots, wbars, w);
            refill_if(p, p.steps[c + 3], wslots, wbars, w);
            c += 4;
            __syncthreads();
        }
        const uint32_t offk = (((lane >> 3) & 1) * 8 + (lane & 7)) * 128 + ((((lane >> 4) & 1) ^ (lane & 7)) << 4);
        const uint32_t offv = (((lane >> 4) & 1) * 8 + (lane & 7)) * 128 + ((((lane >> 3) & 1) ^ (lane & 7)) << 4);
        a.mv = pin((((lane >> 2) ^ (lane >> 1)) & 1) - 1u);
        uint32_t f[32];
        if (layer & 1) {
            const uint32_t e = p.steps[c];
            wait_step(wbars, e);
            load_k(f, slot_addr(wslots, e) + offk);
            asm volatile("" :: "r"(f[31]), "r"(f[27]) : "memory");
            refill_if(p, e, wslots, wbars, w);
        } else {
#pragma unroll
            for (int i = 0; i < 32; i++) f[i] = 0u;
        }
        {
            const float* qsrc = pin(&p.xc->q[h * 16 + 2 * w][2 * lane]);
            const uint32_t qd = pin(smem + OFF_RED + ((lane >> 4) * 32 + 4 * ((w >> 1) + 4 * (w & 1)) + (lane & 3)) * 16 + (lane & 12));
            uint32_t v0, v1;
            int it = 0;
            do { ld_rlx8(v0, v1, qsrc); } while (!__all_sync(FULL, ((v0 ^ tag) & 3u) == 0u) && ++it < SPIN_LIMIT);
            sts(qd, __uint_as_float(pack_bf16(__uint_as_float(v0), __uint_as_float(v1))));
            __syncthreads();
            lds4(reinterpret_cast<float*>(a.qf), smem + OFF_RED + lane * 16);
            lds4(reinterpret_cast<float*>(a.qf + 4), smem + OFF_RED + 512 + lane * 16);
        }
        TSTAMP(3 + layer * 8);
        if (layer & 1) {
            const uint32_t ek1 = p.steps[c + 1], ev0 = p.steps[c + 2], ev = p.steps[c + 3];
            uint32_t b[8];
            float s[8];
            qk(a, f, s);
            wait_step(wbars, ek1);
            load_k(f, slot_addr(wslots, ek1) + offk);
            qk(a, f, s + 4);
            refill(p, ek1, wslots, wbars, w);
#pragma unroll
            for (int i = 0; i < 8; i++) s[i] += __shfl_xor_sync(FULL, s[i], 6);
            float t0 = fmaxf(fmaxf(s[0], s[2]), fmaxf(s[4], s[6])), t1 = fmaxf(fmaxf(s[1], s[3]), fmaxf(s[5], s[7]));
#pragma unroll
            for (int d = 4; d <= 16; d <<= 1) {
                t0 = fmaxf(t0, __shfl_xor_sync(FULL, t0, d));
                t1 = fmaxf(t1, __shfl_xor_sync(FULL, t1, d));
            }
            a.n0 = -SCALE_LOG2E * t0; a.n1 = -SCALE_LOG2E * t1;
            a.l0 = a.l1 = 0.f;
#pragma unroll
            for (int i = 0; i < 8; i++) s[i] = fmaf(s[i], SCALE_LOG2E, (i & 1) ? a.n1 : a.n0);
            wait_step(wbars, ev0);
            load_v(f, slot_addr(wslots, ev0) + offv);
            probs(a, s, b, a.l0, a.l1);
            probs(a, s + 4, b + 4, a.l0, a.l1);
#pragma unroll
            for (int i = 0; i < 16; i++) a.o[i] = 0.f;
            pv(a, f, b);
            refill(p, ev0, wslots, wbars, w);
            wait_step(wbars, ev);
            load_v(f, slot_addr(wslots, ev) + offv);
            pv(a, f, b + 4);
        } else {
#pragma unroll
            for (int i = 0; i < 16; i++) a.o[i] = 0.f;
            a.n0 = a.n1 = INFINITY;
            a.l0 = a.l1 = 0.f;
            uint32_t ek = p.steps[c], ev = p.steps[c + 1];
            bool kready = false;
#pragma unroll 1
            for (;;) {
                float s[4];
                uint32_t b[4];
                c += 2;
                const uint32_t nk = p.steps[c], nv = p.steps[c + 1];
                if (ek & STEP_PACK) {
                    const uint32_t r = (ek >> 21) & 3u, id = (ek >> 23) & 7u;
                    const uint32_t bb = lds_u16(smem + OFF_META + w * 16 + 2 * id), l16 = lane_id() * 16;
                    const uint32_t ak = slot_addr(wslots, ek), av = slot_addr(wslots, ev);
                    const uint32_t bk = (127u + (bb & 0xffu)) * 0x00800080u, bv = (127u + (bb >> 8)) * 0x00800080u;
                    const uint32_t again = __ballot_sync(FULL, ((bb >> (l16 >> 1)) & 0xffu) == 0xffu) & 3u;
                    asm volatile("{\n.reg .pred p, q;\nelect.sync _|p, 0xffffffff;\n"
                                 "setp.eq.and.u32 q, %2, 0, p;\n@q mbarrier.arrive.shared::cta.b64 _, [%0];\n"
                                 "setp.eq.and.u32 q, %3, 0, p;\n@q mbarrier.arrive.shared::cta.b64 _, [%1];\n}"
                                 :: "r"(slot_bar(wbars, ek)), "r"(slot_bar(wbars, ev)), "r"(again & 1u), "r"(again & 2u) : "memory");
#pragma unroll
                    for (int i = 0; i < NRF; i++) if (r == i) {
                        unpack_tile(rf[2 * i], ak + l16, bk);
                        unpack_tile(rf[2 * i + 1], av + l16, bv);
                    }
                    __syncwarp();
                    if ((patch >> 29) == id) sts_u16(((patch >> 28) & 1u ? av : ak) + ((patch >> 16) & 0xfffu), patch);
                    __syncwarp();
                    if (again) {
                        asm volatile("fence.proxy.async.shared::cta;" ::: "memory");
                        refill(p, ((again & 1u) << 4) | (id << 9) | ((ek & 7u) << 16), wslots, wbars, w);
                        refill(p, ((again & 2u) << 3) | (1 << 6) | (id << 9) | ((ev & 7u) << 16), wslots, wbars, w);
                    }
                }
                if (!kready) wait_step(wbars, ek);
                load_k(f, slot_addr(wslots, ek) + offk);
                qk(a, f, s);
                refill(p, ek, wslots, wbars, w);
                const bool vready = mbar_test(slot_bar(wbars, ev), (ev >> 3) & 1u);
                softmax_step(a, s, b);
                if (!vready) wait_step(wbars, ev);
                load_v(f, slot_addr(wslots, ev) + offv);
                kready = mbar_test(slot_bar(wbars, nk), (nk >> 3) & 1u);
                pv(a, f, b);
                refill(p, ev, wslots, wbars, w);
                if (ev & STEP_FENCE) {
                    const int ln = lane_id();
                    if (ev & STEP_PACK) {
                        const uint32_t id = (ev >> 23) & 7u;
                        __syncwarp();
#pragma unroll 1
                        for (int i = 0; i < 2; i++) {
                            const uint32_t e = i ? ev : ek;
                            pack_tile(slot_addr(wslots, e), wslots + ((e >> 16) & 0x7c00u), smem + OFF_META + w * 16 + 2 * id + i, 2 * id + i, patch, ln);
                        }
                    }
                    if (ev & STEP_TOREG) {
                        const uint32_t r = (ev >> 21) & 3u;
                        const uint32_t ak = wslots + ((ek >> 16) & 0x7c00u) + ln * 16, av = wslots + ((ev >> 16) & 0x7c00u) + ln * 16;
#pragma unroll
                        for (int i = 0; i < NRF; i++) if (r == i) {
#pragma unroll
                            for (int j = 0; j < 6; j++) { lds4u(&rf[2 * i][4 * j], ak + j * 512); lds4u(&rf[2 * i + 1][4 * j], av + j * 512); }
                        }
                    }
                    asm volatile("fence.proxy.async.shared::cta;" ::: "memory");
                    __syncwarp();
#pragma unroll 1
                    for (int i = 0; i < 2; i++) refill_if(p, p.post[layer >> 1][(ev >> 23) & 7u][i], wslots, wbars, w);
                }
                if (ev & STEP_LAST) break;
                ek = nk; ev = nv;
            }
        }
        c = p.last[layer] + 1;
        const uint32_t ev = p.steps[c++];
        lane = lane_id();
        const int g = lane >> 2, t = lane & 3, half = lane >> 4, c16 = lane & 15;
        TSTAMP(4 + layer * 8);
        uint32_t v[8][4], mj, lj;
        const float* src = pin(&p.xc->part[h * 16 + half][w][4 * c16]);
        const float* ssrc = pin(&p.xc->part[h * 16 + c16][w][64]);
        {
            a.l0 += __shfl_xor_sync(FULL, a.l0, 4);
            a.l1 += __shfl_xor_sync(FULL, a.l1, 4);
            a.l0 += __shfl_xor_sync(FULL, a.l0, 8);
            a.l1 += __shfl_xor_sync(FULL, a.l1, 8);
            const uint32_t o0 = slot_addr(wslots, ev) + ((4 * (t & 1) + (t >> 1)) * 96 + 8 * t + g) * 4;
#pragma unroll
            for (int i = 0; i < 4; i++) {
                sts(o0 + i * 64, a.o[4 * i]);
                sts(o0 + i * 64 + 192 * 4, a.o[4 * i + 1]);
                sts(o0 + i * 64 + 32, a.o[4 * i + 2]);
                sts(o0 + i * 64 + 192 * 4 + 32, a.o[4 * i + 3]);
            }
            a.l0 += __shfl_xor_sync(FULL, a.l0, 16);
            a.l1 += __shfl_xor_sync(FULL, a.l1, 16);
            if (lane < 2) {
                const uint32_t ml = smem + OFF_ML + lane * 128 + w * 4;
                sts(ml, -a.n0); sts(ml + 64, -a.n1); sts(ml + 32, a.l0); sts(ml + 96, a.l1);
            }
            float* dst = pin(&p.xc->part[cta][w][4 * lane]);
            const uint32_t mlr = pin(smem + OFF_ML + (w >> 1) * 64 + half * 16);
            const uint32_t ro = pin(slot_addr(smem, ev) + half * (4 * NSLOT * TILE) + (w * 96 + 8 * ((w >> 2) + 2 * (w & 1)) + 4 * c16) * 4);
            __syncthreads();
            float m[8], l[4], u[4][4];
            lds4(m, mlr);
            lds4(m + 4, mlr ^ 16u);
#pragma unroll
            for (int i = 0; i < 4; i++) lds4(u[i], ro + i * (NSLOT * TILE));
            lds4(l, mlr + 32);
            const float M = fmaxf(fmaxf(fmaxf(m[0], m[1]), fmaxf(m[2], m[3])), fmaxf(fmaxf(m[4], m[5]), fmaxf(m[6], m[7])));
            float z[4], r[4];
#pragma unroll
            for (int i = 0; i < 4; i++) z[i] = ex2(m[i] - M);
#pragma unroll
            for (int k = 0; k < 4; k++) r[k] = fmaf(z[0], u[0][k], z[1] * u[1][k]) + fmaf(z[2], u[2][k], z[3] * u[3][k]);
            float L = fmaf(z[0], l[0], z[1] * l[1]) + fmaf(z[2], l[2], z[3] * l[3]);
#pragma unroll
            for (int k = 0; k < 4; k++) r[k] += __shfl_xor_sync(FULL, r[k], 16);
            L += __shfl_xor_sync(FULL, L, 16);
            if (lane <= 16) st_rlx16(dst, tagged(selp(M, r[0], half), tag), __float_as_uint(selp(L, r[1], half)), __float_as_uint(r[2]), __float_as_uint(r[3]));
            TSTAMP(5 + layer * 8);
            ld_rlx8(mj, lj, ssrc);
#pragma unroll
            for (int j = 0; j < 8; j++) ld_rlx16(v[j], src + j * (2 * NW * 96));
            asm volatile("fence.proxy.async.shared::cta;" ::: "memory");
            __syncthreads();
            refill_if(p, ev, wslots, wbars, w);
            refill_if(p, p.steps[c], wslots, wbars, w);
        }
        {
            const uint32_t e = p.steps[c + 1];
            int it = 0;
            for (;;) {
                uint32_t bad = mj ^ tag;
#pragma unroll
                for (int j = 0; j < 8; j++) bad |= v[j][0] ^ tag;
                if (__all_sync(FULL, (bad & 3u) == 0u) || ++it >= SPIN_LIMIT) break;
                if ((mj ^ tag) & 3u) ld_rlx8(mj, lj, ssrc);
#pragma unroll
                for (int j = 0; j < 8; j++)
                    if ((v[j][0] ^ tag) & 3u) ld_rlx16(v[j], src + j * (2 * NW * 96));
            }
            TSTAMP(6 + layer * 8);
            const int key = (int)mj ^ (((int)mj >> 31) & 0x7fffffff);
            const int kmax = __reduce_max_sync(FULL, key);
            const float M = __int_as_float(kmax ^ ((kmax >> 31) & 0x7fffffff));
            const float fo = ex2(__uint_as_float(mj) - M);
            float fj[8], r[4];
#pragma unroll
            for (int j = 0; j < 8; j++) fj[j] = __shfl_sync(FULL, fo, 2 * j + half);
#pragma unroll
            for (int k = 0; k < 4; k++) {
                float r0 = fj[0] * __uint_as_float(v[0][k]), r1 = fj[1] * __uint_as_float(v[1][k]);
#pragma unroll
                for (int j = 2; j < 8; j += 2) { r0 = fmaf(fj[j], __uint_as_float(v[j][k]), r0); r1 = fmaf(fj[j + 1], __uint_as_float(v[j + 1][k]), r1); }
                r[k] = r0 + r1;
            }
            const float y0 = selp(r[2], r[0], half) + __shfl_xor_sync(FULL, selp(r[0], r[2], half), 16);
            const float y1 = selp(r[3], r[1], half) + __shfl_xor_sync(FULL, selp(r[1], r[3], half), 16);
            refill_if(p, p.steps[c + 2], wslots, wbars, w);
            wait_step(wbars, e);
            uint32_t fw[8][4];
            gemv_load(fw, slot_addr(wslots, e), lane);
            float L = fo * __uint_as_float(lj);
#pragma unroll
            for (int d = 1; d < 16; d <<= 1) L += __shfl_xor_sync(FULL, L, d);
            float y, unused;
            gemv_mma<false>(fw, pack_bf16(y0, y1), y, unused, nullptr, lane);
            float* dst = pin(&p.xc->x[layer & 1][cta][4 * lane]);
            sts(smem + OFF_RED + w * 128 + (8 * t + g) * 4, y * rcp(L));
            __syncthreads();
            if (w == 0) {
                float u[8][4];
#pragma unroll
                for (int i = 0; i < 8; i++) lds4(u[i], smem + OFF_RED + i * 128 + (lane & 7) * 16);
#pragma unroll
                for (int k = 0; k < 4; k++) r[k] = ((u[0][k] + u[1][k]) + (u[2][k] + u[3][k])) + ((u[4][k] + u[5][k]) + (u[6][k] + u[7][k]));
                if (lane < 8) st_rlx16(dst, tagged(r[0], tag), __float_as_uint(r[1]), __float_as_uint(r[2]), __float_as_uint(r[3]));
            }
            TSTAMP(7 + layer * 8);
            refill_if(p, e, wslots, wbars, w);
            refill_if(p, p.steps[c + 3], wslots, wbars, w);
            __syncthreads();
        }
    }
    if (cta == 0) {
        const float* src = &p.xc->x[1][16 * (lane >> 4) + 2 * w][4 * (lane & 15)];
        uint32_t v[4][4];
        int it = 0;
        do {
#pragma unroll
            for (int j = 0; j < 4; j++) ld_rlx16(v[j], src + j * 1024);
        } while (!__all_sync(FULL, ((v[0][0] | v[1][0] | v[2][0] | v[3][0]) & 3u) == 0u) && ++it < SPIN_LIMIT);
        reinterpret_cast<uint32_t*>(p.out)[32 * w + 2 * (lane & 15) + (lane >> 4)] = add_residual(xp, v, lane >> 4);
        TSTAMP(32);
    }
}

typedef CUresult (*EncodeFn)(CUtensorMap*, CUtensorMapDataType, cuuint32_t, void*, const cuuint64_t*, const cuuint64_t*,
                             const cuuint32_t*, const cuuint32_t*, CUtensorMapInterleave, CUtensorMapSwizzle,
                             CUtensorMapL2promotion, CUtensorMapFloatOOBfill);

void encode5d(EncodeFn enc, CUtensorMap* m, const void* ptr, uint32_t cols, uint32_t rows, uint32_t nchunk,
              uint64_t srow, uint64_t schunk, uint64_t ss, uint64_t sh, CUtensorMapSwizzle sw, CUtensorMapL2promotion promo) {
    cuuint64_t dims[5] = {cols, rows, nchunk, 16, 8};
    cuuint64_t strides[4] = {srow, schunk, ss, sh};
    cuuint32_t box[5] = {cols, rows, 1, 1, 1};
    cuuint32_t es[5] = {1, 1, 1, 1, 1};
    CUresult r = enc(m, CU_TENSOR_MAP_DATA_TYPE_BFLOAT16, 5, const_cast<void*>(ptr), dims, strides, box, es,
        CU_TENSOR_MAP_INTERLEAVE_NONE, sw, promo, CU_TENSOR_MAP_FLOAT_OOB_FILL_NONE);
    (void)r;
}

struct Sched {
    unsigned long long ord1 = 0x09a3214ef85cdb67;
    unsigned long long ord3 = 0x67c1a42e380f5b9d;
    unsigned long long l2 = 0x3fff0000;
    int pw = 2, pk = 2;
    int keepw = 1;
    int hold = 3;
    int nearly = 2;
    int promoB = 17;
    int promoW = 0;
    int d0 = 4;
    int dr = 3;
    int d1 = 2;
    int d3 = 5;
    int ch1 = 111111111, ch2 = 111102100, ch3 = 231245166;
};

#define CHECK(c)
void build_schedule(Params& p, const Sched& sc) {
    struct Item { int map, tile, promote; };
    Item items[96];
    int n = 0;
    auto add = [&](int map, int tile, int promote) { items[n] = Item{map, tile, promote}; return n++; };
    auto dig = [](int v, int i) { for (int k = 8; k > i; k--) v /= 10; return v % 10; };
    int c1[32], n1 = 0, c3[32], n3 = 0;
    const int wq1 = add(M_WQA, 0, 0);
    for (int sp = 0; sp < 16; sp++) {
        const int pr = (sc.ord1 >> (60 - 4 * sp)) & 15;
        c1[n1++] = add(0, pr, (sc.l2 >> (2 * pr)) & 1);
        c1[n1++] = add(1, pr, (sc.l2 >> (2 * pr + 1)) & 1);
    }
    auto tile_of = [&](int it) { return 2 * items[it].tile + items[it].map; };
    auto keep1 = [&](int it) { return tile_of(it) == 12 || tile_of(it) == 14 || (tile_of(it) == 13 && !sc.keepw); };
    const int tail1 = n;
    add(M_WOA, 0, sc.promoW & 1);
    add(M_WQB, 0, sc.promoB & 1);
    for (int u = 0; u < 4; u++) add(M_KB + (u >> 1), u & 1, (sc.promoB >> (1 + u)) & 1);
    add(M_WOB, 0, (sc.promoB >> 5) & 1);
    const int wq3 = sc.keepw ? wq1 : add(M_WQA, 0, 0);
    for (int sp = 0; sp < 16; sp++) {
        const int pr = (sc.ord3 >> (60 - 4 * sp)) & 15;
        for (int u = 2 * pr; u < 2 * pr + 2; u++) {
            int it = -1;
            for (int i = 0; i < n1; i++) if (keep1(c1[i]) && tile_of(c1[i]) == u) it = c1[i];
            c3[n3++] = pr < 6 ? -1 - u : (it >= 0 ? it : add(u & 1, u >> 1, 0));
        }
    }
    const int tail3 = n;
    add(M_WOA, 0, 0); add(M_WQB, 0, 0);
    for (int u = 0; u < 4; u++) add(M_KB + (u >> 1), u & 1, 0);
    add(M_WOB, 0, 0);
    int slot_of[96], pending[96] = {0}, par[NSLOT] = {0}, ic = NFIRST, c = 0, nq = NFIRST, reserve = 0;
    unsigned fre = 0x7f & ~((1u << NFIRST) - 1), avoid = 0;
    for (int i = 0; i < NFIRST; i++) { slot_of[i] = i; pending[i] = 1; }
    for (int i = 0; i < NSTEP; i++) p.steps[i] = 0;
    auto nfree = [&]() { return __builtin_popcount(fre & ~avoid); };
    auto take = [&]() { const int s = __builtin_ctz(fre & ~avoid); fre &= ~(1u << s); return s; };
    auto load = [&](int depth) -> uint32_t {
        if (!(ic < n && nfree() > reserve && nq < depth)) return 0;
        const Item& it = items[ic];
        const int dst = slot_of[ic] = take();
        pending[ic++] = 1; nq++;
        return 16 | (it.promote << 5) | (it.map << 6) | (it.tile << 9) | (dst << 16);
    };
    auto extra = [&](int depth) { p.steps[c++] = load(depth); };
    auto release = [&](int slot) { par[slot] ^= 1; fre |= 1u << slot; };
    auto consume = [&](int it, bool keep) -> uint32_t {
        CHECK(it < ic);
        if (it >= ic) return 0;
        const int slot = slot_of[it];
        if (pending[it]) { pending[it] = 0; nq--; }
        const uint32_t e = slot | (par[slot] << 3);
        if (!keep) release(slot);
        return e;
    };
    auto step = [&](int it, bool keep, int depth) { const uint32_t e = consume(it, keep); p.steps[c++] = e | load(depth); };
    auto atleast1 = [](int d) { return d < 1 ? 1 : d; };
    int layer = 0;
    auto chain = [&](int t0, bool keep0, int t1, int wo, int wq, int d) {
        { const uint32_t e = consume(t0, keep0); p.steps[c++] = e | load(atleast1(dig(d, 0))); }
        p.steps[c++] = consume(t1, false) | STEP_LAST;
        p.last[layer++] = c - 1;
        extra(atleast1(dig(d, 1))); p.steps[c - 1] |= p.steps[c - 2] & 7;
        p.steps[c++] = load(dig(d, 1));
        const int at = c++;
        p.steps[c++] = load(dig(d, 2));
        p.steps[at] = consume(wo, false);
        p.steps[at] |= load(wq >= ic ? atleast1(dig(d, 3)) : dig(d, 3));
        p.steps[c++] = load(dig(d, 3));
        if (wq < 0) return;
        p.first[layer] = c;
        step(wq, false, dig(d, 4));
        p.steps[c++] = load(dig(d, 5));
        p.steps[c++] = load(atleast1(dig(d, 6)));
        p.steps[c++] = load(dig(d, 6));
    };
    const unsigned area[2] = {0x60, 0x30};
    p.first[0] = 0;
    step(wq1, sc.keepw, 0); extra(0); extra(sc.d0); extra(sc.d0);
    for (int u = 0; u < 30; u++) {
        for (int i = u; i < u + 8 && i < 32; i++)
            if (items[c1[i]].tile == 4 || items[c1[i]].tile == 5) avoid |= area[items[c1[i]].tile - 4];
        if (items[c1[u + 2]].tile == 6 || (u + 4 < 32 && items[c1[u + 4]].tile == 6)) avoid |= 0x70;
        const int depth = u < 2 ? sc.d0 : (u < 2 * sc.nearly ? sc.dr : sc.d1), pr = items[c1[u]].tile;
        if (pr < 6) {
            step(c1[u], true, depth);
            const int at = pr < 4 ? 4 * slot_of[c1[u]] : 22 - 6 * (pr - 4) + 3 * (u & 1);
            p.steps[c - 1] |= at << 26;
            if (u & 1) {
                p.steps[c - 1] |= STEP_FENCE | STEP_PACK | (pr << 23) | (pr < 4 ? STEP_TOREG | (pr << 21) : 0);
                if (pr >= 4) CHECK((fre & area[pr - 4]) == area[pr - 4]);
                release(slot_of[c1[u - 1]]); release(slot_of[c1[u]]);
                p.post[0][pr][0] = load(depth); p.post[0][pr][1] = load(depth);
            }
        } else step(c1[u], keep1(c1[u]), depth);
    }
    CHECK(avoid == 0x70 && (fre & 0x70) == 0x70 && items[c1[30]].tile == 7);
    chain(c1[30], true, c1[31], tail1, tail1 + 1, sc.ch1);
    step(tail1 + 2, false, atleast1(dig(sc.ch1, 7))); step(tail1 + 3, false, atleast1(dig(sc.ch1, 8)));
    chain(tail1 + 4, false, tail1 + 5, tail1 + 6, wq3, sc.ch2);
    int regset[6] = {0, 1, 2, 3, -1, -1}, moved = 0;
    for (int u = 0; u < n3 - 2; u++) {
        int left = 0;
        for (int i = u + 1; i < n3; i++) left += c3[i] >= 0;
        const int cap = left + dig(sc.ch3, 0) - 1, depth = sc.d3 < cap ? sc.d3 : cap;
        const int nxt = (u | 1) + 1;
        if (c3[u] < 0) {
            CHECK(nfree() >= 2);
            if (nfree() < 2) return;
            const int pr = (-1 - c3[u]) >> 1, sk = take(), sv = take();
            CHECK(regset[pr] >= 0);
            reserve = 0;
            p.steps[c++] = sk | (par[sk] << 3) | STEP_PACK | (regset[pr] << 21) | (pr << 23) | load(depth);
            p.steps[c++] = sv | (par[sv] << 3) | STEP_FENCE | (pr << 23) | load(depth);
            u++;
            if (moved < 2) {
                p.steps[c - 2] |= (22 - 6 * moved) << 26;
                p.steps[c - 1] |= STEP_TOREG | (regset[pr] << 21) | ((25 - 6 * moved) << 26);
                regset[4 + moved] = regset[pr];
                avoid = moved ? 0 : 0x30;
                moved++;
            }
            release(sk); release(sv);
            reserve = nxt < n3 && c3[nxt] < 0 ? 2 : (nxt + 2 < n3 && c3[nxt + 2] < 0 ? sc.hold : 0);
            p.post[1][pr][0] = load(depth); p.post[1][pr][1] = load(depth);
        } else {
            reserve = nxt < n3 && c3[nxt] < 0 ? ((u & 1) ? 2 : 1) : 0;
            step(c3[u], false, depth);
        }
    }
    reserve = 0;
    CHECK(c3[n3 - 1] >= 0);
    chain(c3[n3 - 2], false, c3[n3 - 1], tail3, tail3 + 1, sc.ch3);
    step(tail3 + 2, false, atleast1(dig(sc.ch3, 7))); step(tail3 + 3, false, atleast1(dig(sc.ch3, 8)));
    chain(tail3 + 4, false, tail3 + 5, tail3 + 6, -1, 777777777);
}

Sched g_sched;

}

extern "C" void kernel_launch(void* const* d_in, const int* in_sizes, int n_in, void* d_out, int out_size) {
    (void)in_sizes; (void)n_in; (void)out_size;
    void* fn = nullptr;
    cudaDriverEntryPointQueryResult qr;
    cudaGetDriverEntryPoint("cuTensorMapEncodeTiled", &fn, cudaEnableDefault, &qr);
    EncodeFn enc = (EncodeFn)fn;
    Params p;
    const CUtensorMapL2promotion pk = (CUtensorMapL2promotion)g_sched.pk, pw = (CUtensorMapL2promotion)g_sched.pw;
    const size_t win = (size_t)28672 * 256;
    encode5d(enc, &p.maps[M_KA], d_in[1], 64, 32, 128, 128, 4096, 512 << 10, 8 << 20, CU_TENSOR_MAP_SWIZZLE_128B, pk);
    encode5d(enc, &p.maps[M_VA], d_in[2], 64, 32, 128, 128, 4096, 512 << 10, 8 << 20, CU_TENSOR_MAP_SWIZZLE_128B, pk);
    encode5d(enc, &p.maps[M_KB], (const char*)d_in[6] + win, 64, 32, 16, 128, 4096, 64 << 10, 8 << 20, CU_TENSOR_MAP_SWIZZLE_128B, pk);
    encode5d(enc, &p.maps[M_VB], (const char*)d_in[7] + win, 64, 32, 16, 128, 4096, 64 << 10, 8 << 20, CU_TENSOR_MAP_SWIZZLE_128B, pk);
    encode5d(enc, &p.maps[M_WQA], d_in[3], 32, 64, 8, 8192, 64 * 8192, 64, 1024, CU_TENSOR_MAP_SWIZZLE_64B, pw);
    encode5d(enc, &p.maps[M_WQB], d_in[8], 32, 64, 8, 8192, 64 * 8192, 64, 1024, CU_TENSOR_MAP_SWIZZLE_64B, pw);
    encode5d(enc, &p.maps[M_WOA], d_in[4], 32, 64, 8, 1024, 64 << 10, 64, 512 << 10, CU_TENSOR_MAP_SWIZZLE_64B, pw);
    encode5d(enc, &p.maps[M_WOB], d_in[9], 32, 64, 8, 1024, 64 << 10, 64, 512 << 10, CU_TENSOR_MAP_SWIZZLE_64B, pw);
    void* xc = nullptr;
    cudaGetSymbolAddress(&xc, g_xchg);
    p.xc = (Xchg*)xc;
    p.x = (const __nv_bfloat16*)d_in[0];
    p.out = (__nv_bfloat16*)d_out;
    build_schedule(p, g_sched);
    cudaFuncSetAttribute(decode_kernel, cudaFuncAttributeMaxDynamicSharedMemorySize, SMEM_BYTES);
    decode_kernel<<<NCTA, NW * 32, SMEM_BYTES, cudaStreamPerThread>>>(p);
}
```
